```python
import torch

def _softmax(x, axis=-1):
    return torch.softmax(x, dim=axis)
def _gelu(x):
    return torch.nn.functional.gelu(x, approximate="tanh")
def _silu(x):
    return torch.nn.functional.silu(x)
def _sigmoid(x):
    return torch.sigmoid(x)
def _layernorm(x, axis=-1, eps=1e-5):
    m = x.mean(dim=axis, keepdim=True)
    v = x.var(dim=axis, keepdim=True, unbiased=False)
    return (x - m) / torch.sqrt(v + eps)
def _scatter_add(tgt, idx, src, axis=0):
    return tgt.clone().index_add_(axis, idx, src)
def _segment_sum(src, seg, n):
    out = torch.zeros((n,) + src.shape[1:], dtype=src.dtype)
    return out.index_add_(0, seg, src)
def _pad(x, pw):
    flat = tuple(v for pair in reversed(pw) for v in pair)
    return torch.nn.functional.pad(x, flat)

kernel_name = 'interleave_layers__gqa_block_cached__gqa_block_cached__decode'

def setup_inputs():

    _w = (lambda a: (lambda t: t.to(torch.bfloat16) if t.is_floating_point() else t)(torch.as_tensor(a)))
    def _A_setup():
        B, Sq, D = 8, 1, 512
        Hq, Hkv, Sk, Dh = 32, 8, 4096, 128
        assert Hq % Hkv == 0, (Hq, Hkv)
        return {
            "x": _w((lambda *s: torch.randn(*s, dtype=torch.bfloat16) * 0.1)(B, Sq, D)),
            "k_cache": _w((lambda *s: torch.randn(*s, dtype=torch.bfloat16) * 0.8)(B, Hkv, Sk, Dh)),
            "v_cache": _w((lambda *s: torch.randn(*s, dtype=torch.bfloat16) * 3.2)(B, Hkv, Sk, Dh)),
            "wq": _w((lambda *s: torch.randn(*s, dtype=torch.bfloat16) * 0.8)(D, Hq * Dh) * (D ** -0.5)),
            "wo": _w((lambda *s: torch.randn(*s, dtype=torch.bfloat16) * 3.2)(Hq * Dh, D) * ((Hq * Dh) ** -0.5)),
        }
    _A_in = _A_setup()

    def _B_setup():
        B, Sq, D = 8, 1, 512
        Hq, Hkv, Sk, Dh = 32, 8, 4096, 128
        assert Hq % Hkv == 0, (Hq, Hkv)
        return {
            "x": _w((lambda *s: torch.randn(*s, dtype=torch.bfloat16) * 0.1)(B, Sq, D)),
            "k_cache": _w((lambda *s: torch.randn(*s, dtype=torch.bfloat16) * 1.6)(B, Hkv, Sk, Dh)),
            "v_cache": _w((lambda *s: torch.randn(*s, dtype=torch.bfloat16) * 1.6)(B, Hkv, Sk, Dh)),
            "wq": _w((lambda *s: torch.randn(*s, dtype=torch.bfloat16) * 1.6)(D, Hq * Dh) * (D ** -0.5)),
            "wo": _w((lambda *s: torch.randn(*s, dtype=torch.bfloat16) * 1.6)(Hq * Dh, D) * ((Hq * Dh) ** -0.5)),
        }
    _B_in = _B_setup()

    return {
        "A_x": _A_in["x"],
        "A_k_cache": _A_in["k_cache"],
        "A_v_cache": _A_in["v_cache"],
        "A_wq": _A_in["wq"],
        "A_wo": _A_in["wo"],
        "B_x": _B_in["x"],
        "B_k_cache": _B_in["k_cache"],
        "B_v_cache": _B_in["v_cache"],
        "B_wq": _B_in["wq"],
        "B_wo": _B_in["wo"],
    }

def reference(A_x, A_k_cache, A_v_cache, A_wq, A_wo, B_x, B_k_cache, B_v_cache, B_wq, B_wo):
    def _A_ref(x, k_cache, v_cache, wq, wo):
        B, Sq, D = x.shape
        Hq, Dh = 32, 128
        Hkv = k_cache.shape[1]
        rep = Hq // Hkv
        q = (lambda x, *d: x.permute(*d))((x @ wq).reshape(B, Sq, Hq, Dh), 0, 2, 1, 3)
        k = (lambda x, n, axis: torch.repeat_interleave(x, n, dim=axis))(k_cache, rep, axis=1)
        v = (lambda x, n, axis: torch.repeat_interleave(x, n, dim=axis))(v_cache, rep, axis=1)
        scores = torch.einsum("bhqd,bhkd->bhqk", q, k) * (Dh ** -0.5)
        p = _softmax(scores, axis=-1)
        o = torch.einsum("bhqk,bhkd->bhqd", p, v)
        return (lambda x, *d: x.permute(*d))(o, 0, 2, 1, 3).reshape(B, Sq, Hq * Dh) @ wo

    def _B_ref(x, k_cache, v_cache, wq, wo):
        B, Sq, D = x.shape
        Hq, Dh = 32, 128
        Hkv = k_cache.shape[1]
        rep = Hq // Hkv
        q = (lambda x, *d: x.permute(*d))((x @ wq).reshape(B, Sq, Hq, Dh), 0, 2, 1, 3)
        k = (lambda x, n, axis: torch.repeat_interleave(x, n, dim=axis))(k_cache, rep, axis=1)
        v = (lambda x, n, axis: torch.repeat_interleave(x, n, dim=axis))(v_cache, rep, axis=1)
        scores = torch.einsum("bhqd,bhkd->bhqk", q, k) * (Dh ** -0.5)
        p = _softmax(scores, axis=-1)
        o = torch.einsum("bhqk,bhkd->bhqd", p, v)
        return (lambda x, *d: x.permute(*d))(o, 0, 2, 1, 3).reshape(B, Sq, Hq * Dh) @ wo

    x = A_x
    x = x + _A_ref(_layernorm(x, axis=-1), A_k_cache, A_v_cache, A_wq, A_wo)
    x = x + _B_ref(_layernorm(x, axis=-1), B_k_cache, B_v_cache, B_wq, B_wo)
    x = x + _A_ref(_layernorm(x, axis=-1), A_k_cache, A_v_cache, A_wq, A_wo)
    x = x + _B_ref(_layernorm(x, axis=-1), B_k_cache, B_v_cache, B_wq, B_wo)
    return x
```

```cpp
#include <cuda_runtime.h>
#include <cuda_bf16.h>
#include <cuda.h>
#include <stdint.h>

namespace {

constexpr int kCtas = 128;
constexpr int kThreads = 384;
constexpr int kPhases = 18;
constexpr int kTile = 8192;
constexpr int kNV = 3;
constexpr int kWin = 4;
constexpr int kWoPitch = 1040;
constexpr long long kWatchdogClocks = 4000000000LL;
constexpr float kScale = 0.08838834764831845f * 1.4426950408889634f;
constexpr uint32_t kOnes = 0x3f803f80u;

constexpr int SM_K = 0;
constexpr int SM_V = SM_K + 8 * kTile;
constexpr int SM_WQ = SM_V + kNV * kTile;
constexpr int SM_WO = SM_WQ + 2 * 32768;
constexpr int SM_P = SM_WO + 2 * 32 * kWoPitch;
constexpr int SM_Q = SM_P + 4096;
constexpr int SM_QP = SM_Q + 2048;
constexpr int SM_ST = SM_QP + 2048;
constexpr int SM_M = SM_ST + 128;
constexpr int SM_O = SM_M + 256;
constexpr int SM_R = SM_O + 128;
constexpr int SM_PR = SM_R + 1024;
constexpr int SM_BAR = SM_PR + 16;
constexpr int BAR_FULLK = SM_BAR;
constexpr int BAR_FULLR = BAR_FULLK + 8 * 8;
constexpr int BAR_EMPTYK = BAR_FULLR + 4 * 8;
constexpr int BAR_FULLV = BAR_EMPTYK + 4 * 8;
constexpr int BAR_EMPTYV = BAR_FULLV + kNV * 8;
constexpr int BAR_FULLW = BAR_EMPTYV + kNV * 8;
constexpr int BAR_DONE = BAR_FULLW + 8 * 8;
constexpr int SM_TOTAL = BAR_DONE + 8;
static_assert(SM_TOTAL <= 232448, "shared memory budget");

constexpr size_t kBoxBytes = 32 * 65536;
constexpr size_t kGrpBytes = 8 * 16384;
__device__ uint4 g_scratch[(kBoxBytes + kGrpBytes + 65536) / 16];

#define TL(i)

struct Maps {
    CUtensorMap k[2], v[2], wq[2];
};

__device__ __forceinline__ void mbar_init(uint32_t a, uint32_t c) {
    asm volatile("mbarrier.init.shared::cta.b64 [%0], %1;" ::"r"(a), "r"(c) : "memory");
}
__device__ __forceinline__ void mbar_expect(uint32_t a, uint32_t bytes) {
    asm volatile("mbarrier.arrive.expect_tx.shared::cta.b64 _, [%0], %1;" ::"r"(a), "r"(bytes) : "memory");
}
__device__ __forceinline__ void mbar_arrive(uint32_t a) {
    asm volatile("mbarrier.arrive.shared::cta.b64 _, [%0];" ::"r"(a) : "memory");
}
__device__ __forceinline__ uint32_t mbar_try(uint32_t a, uint32_t parity) {
    uint32_t ok;
    asm volatile("{.reg .pred p; mbarrier.try_wait.parity.shared::cta.b64 p, [%1], %2; selp.u32 %0, 1, 0, p;}"
                 : "=r"(ok) : "r"(a), "r"(parity) : "memory");
    return ok;
}
__device__ __forceinline__ void mbar_wait(uint32_t a, uint32_t parity) {
    while (!mbar_try(a, parity)) {}
}
__device__ __forceinline__ void tma_kv(uint32_t dst, const CUtensorMap* m, int group, uint32_t bar, uint64_t pol) {
    asm volatile("cp.async.bulk.tensor.4d.shared::cluster.global.mbarrier::complete_tx::bytes.L2::cache_hint"
                 " [%0], [%1, {%3, %3, %3, %4}], [%2], %5;"
                 ::"r"(dst), "l"(m), "r"(bar), "r"(0), "r"(group), "l"(pol) : "memory");
}
__device__ __forceinline__ void tma_2d(uint32_t dst, const CUtensorMap* m, int x, int y, uint32_t bar, uint64_t pol) {
    asm volatile("cp.async.bulk.tensor.2d.shared::cluster.global.mbarrier::complete_tx::bytes.L2::cache_hint"
                 " [%0], [%1, {%3, %4}], [%2], %5;"
                 ::"r"(dst), "l"(m), "r"(bar), "r"(x), "r"(y), "l"(pol) : "memory");
}
__device__ __forceinline__ void bulk_1d(uint32_t dst, const void* src, uint32_t bytes, uint32_t bar, uint64_t pol) {
    asm volatile("cp.async.bulk.shared::cluster.global.mbarrier::complete_tx::bytes.L2::cache_hint"
                 " [%0], [%1], %2, [%3], %4;"
                 ::"r"(dst), "l"(src), "r"(bytes), "r"(bar), "l"(pol) : "memory");
}
__device__ __forceinline__ uint64_t policy_first() {
    uint64_t p;
    asm volatile("createpolicy.fractional.L2::evict_first.b64 %0, 1.0;" : "=l"(p));
    return p;
}
__device__ __forceinline__ uint64_t policy_normal() {
    uint64_t p;
    asm volatile("createpolicy.fractional.L2::evict_normal.b64 %0, 1.0;" : "=l"(p));
    return p;
}
__device__ __forceinline__ void st_pkt(char* p, uint32_t a, uint32_t b, uint32_t c, uint32_t d) {
    asm volatile("{.reg .b128 r; .reg .b64 lo, hi; mov.b64 lo, {%1, %2}; mov.b64 hi, {%3, %4}; mov.b128 r, {lo, hi};"
                 " st.relaxed.gpu.global.b128 [%0], r;}"
                 ::"l"(p), "r"(a), "r"(b), "r"(c), "r"(d) : "memory");
}
__device__ __forceinline__ uint4 ld_pkt(const char* p) {
    uint4 v;
    asm volatile("{.reg .b128 r; .reg .b64 lo, hi; ld.relaxed.gpu.global.b128 r, [%4]; mov.b128 {lo, hi}, r;"
                 " mov.b64 {%0, %1}, lo; mov.b64 {%2, %3}, hi;}"
                 : "=r"(v.x), "=r"(v.y), "=r"(v.z), "=r"(v.w) : "l"(p) : "memory");
    return v;
}
__device__ __forceinline__ void ldsm4(uint32_t* r, uint32_t a) {
    asm volatile("ldmatrix.sync.aligned.m8n8.x4.shared.b16 {%0, %1, %2, %3}, [%4];"
                 : "=r"(r[0]), "=r"(r[1]), "=r"(r[2]), "=r"(r[3]) : "r"(a));
}
__device__ __forceinline__ void ldsm4t(uint32_t* r, uint32_t a) {
    asm volatile("ldmatrix.sync.aligned.m8n8.x4.trans.shared.b16 {%0, %1, %2, %3}, [%4];"
                 : "=r"(r[0]), "=r"(r[1]), "=r"(r[2]), "=r"(r[3]) : "r"(a));
}
__device__ __forceinline__ uint32_t movm(uint32_t a) {
    uint32_t d;
    asm volatile("movmatrix.sync.aligned.m8n8.trans.b16 %0, %1;" : "=r"(d) : "r"(a));
    return d;
}
__device__ __forceinline__ void mma(float* c, uint32_t a0, uint32_t a1, uint32_t a2, uint32_t a3, uint32_t b0, uint32_t b1) {
    asm("mma.sync.aligned.m16n8k16.row.col.f32.bf16.bf16.f32 {%0, %1, %2, %3}, {%4, %5, %6, %7}, {%8, %9}, {%0, %1, %2, %3};"
        : "+f"(c[0]), "+f"(c[1]), "+f"(c[2]), "+f"(c[3])
        : "r"(a0), "r"(a1), "r"(a2), "r"(a3), "r"(b0), "r"(b1));
}
__device__ __forceinline__ void mma(float* c, const uint32_t* a, uint32_t b0, uint32_t b1) {
    mma(c, a[0], a[1], a[2], a[3], b0, b1);
}
__device__ __forceinline__ uint32_t pack_bf16(float lo, float hi) {
    uint32_t d;
    asm("cvt.rn.bf16x2.f32 %0, %1, %2;" : "=r"(d) : "f"(hi), "f"(lo));
    return d;
}
__device__ __forceinline__ float bf_lo(uint32_t v) { return __uint_as_float(v << 16); }
__device__ __forceinline__ float bf_hi(uint32_t v) { return __uint_as_float(v & 0xffff0000u); }
__device__ __forceinline__ float ex2(float x) {
    float y;
    asm("ex2.approx.ftz.f32 %0, %1;" : "=f"(y) : "f"(x));
    return y;
}
__device__ __forceinline__ void bar_sync(int id) { asm volatile("bar.sync %0, 256;" ::"r"(id) : "memory"); }
__device__ __forceinline__ void bar_arrive(int id) { asm volatile("bar.arrive %0, 256;" ::"r"(id) : "memory"); }
__device__ __forceinline__ float pick4(const float* v, int i) {
    float a = (i & 1) ? v[1] : v[0];
    float b = (i & 1) ? v[3] : v[2];
    return (i & 2) ? b : a;
}

struct Ctx {
    char* sm;
    uint32_t sb;
    char* box;
    char* grp;
    const __nv_bfloat16* x0;
    __nv_bfloat16* out;
    int h, c, w, lane;
    uint32_t side, gside;
    uint32_t xa, xb;
    float cs[2][4];
    int vslot;
    uint32_t vpar;
};

__device__ __forceinline__ void pv_tile(const Ctx& cx, uint32_t vaddr, int tile, int slot, float m0, float m1,
                                        float* acc, float* lsum) {
    const int g = cx.lane >> 2, t = cx.lane & 3;
    uint32_t a0[4], a1[4];
    ldsm4t(a0, vaddr);
    ldsm4t(a1, vaddr + 4096);
    uint4 pf = make_uint4(0, 0, 0, 0);
    if ((g >> 2) == slot) pf = *reinterpret_cast<const uint4*>(cx.sm + SM_P + tile * 512 + cx.lane * 16);
    const float2 mt = *reinterpret_cast<const float2*>(cx.sm + SM_M + t * 64 + tile * 8);
    float o[4] = {0.f, 0.f, 0.f, 0.f}, l[4] = {0.f, 0.f, 0.f, 0.f};
    mma(o, a0, pf.x, pf.y);
    mma(l, kOnes, kOnes, kOnes, kOnes, pf.x, pf.y);
    mma(o, a1, pf.z, pf.w);
    mma(l, kOnes, kOnes, kOnes, kOnes, pf.z, pf.w);
    const float s0 = ex2(mt.x - m0), s1 = ex2(mt.y - m1);
    if ((t >> 1) == slot) {
        acc[0] = fmaf(s0, o[0], acc[0]);
        acc[1] = fmaf(s1, o[1], acc[1]);
        acc[2] = fmaf(s0, o[2], acc[2]);
        acc[3] = fmaf(s1, o[3], acc[3]);
        lsum[0] = fmaf(s0, l[0], lsum[0]);
        lsum[1] = fmaf(s1, l[1], lsum[1]);
    }
}

__device__ __forceinline__ void send_x(const Ctx& cx, uint32_t tag) {
    const int cp = cx.w * 4 + (cx.lane >> 3);
    const int owner = (cx.h * 16 + cx.c) >> 2;
    st_pkt(cx.grp + (cp >> 1) * 16384 + 8192 + (cp & 1) * 4096 + owner * 128 + (cx.lane & 7) * 16,
           cx.xa, cx.xb, tag, cx.side);
}

template <int T>
__device__ __forceinline__ void phase(Ctx& cx, const Maps& maps, const int p, uint32_t (&bank)[64]) {
    const int w = cx.w, lane = cx.lane, g = lane >> 2, t = lane & 3, mi = lane >> 3, r = lane & 7;
    const int tid = w * 32 + lane;
    const int cta = cx.h * 16 + cx.c;
    const uint32_t tag = p + 1;
    const bool actF = p < 16, actS = p >= 2;
    const int slotF = (p >> 1) & 1, slotS = slotF ^ 1;
    const bool owner = (cx.c & 3) == 0;
    uint32_t sideO, sideD;

    uint32_t nxa = 0, nxb = 0;
    if (T == 1 && owner && w < 4 && p < 15) {
        const uint32_t* src = reinterpret_cast<const uint32_t*>(cx.x0 + ((p >> 1) + 1) * 512 + (cta >> 2) * 16);
        nxa = __ldg(src + t);
        nxb = __ldg(src + 4 + t);
    }

    {
        TL(0);
        uint32_t wf[4][2][4];
        if (p < 2) {
            mbar_wait(cx.sb + BAR_FULLW + (4 * T) * 8, 0);
            mbar_wait(cx.sb + BAR_FULLW + (4 * T + 1) * 8, 0);
        }
        const uint32_t wa = cx.sb + SM_WQ + T * 32768 + (64 * w + (mi >> 1) * 8 + r) * 64 + (((mi & 1) ^ (r >> 1)) << 4);
#pragma unroll
        for (int i = 0; i < 4; i++) {
            ldsm4t(wf[i][0], wa + i * 1024);
            ldsm4t(wf[i][1], (wa ^ 32) + i * 1024);
        }
        float* qp = reinterpret_cast<float*>(cx.sm + SM_QP);
        const int qpw = w * 64 + (t & 1) * 16 + (g >> 1) * 4 + (g & 1) + (t & 2);
        const int qpr = ((lane >> 2) & 1) * 32 + ((lane >> 3) & 1) * 16 + t * 4;
        if (p < 2) {
            float a0[4] = {0.f, 0.f, 0.f, 0.f}, a1[4] = {0.f, 0.f, 0.f, 0.f};
#pragma unroll
            for (int i = 0; i < 4; i++) {
                mma(a0, wf[i][0], kOnes, kOnes);
                mma(a1, wf[i][1], kOnes, kOnes);
            }
            qp[qpw] = pick4(a0, t);
            qp[qpw + 32] = pick4(a1, t);
            bar_sync(1);
            float s[4] = {0.f, 0.f, 0.f, 0.f};
#pragma unroll
            for (int i = 0; i < 8; i++) {
                const float4 v = *reinterpret_cast<const float4*>(qp + i * 64 + qpr);
                s[0] += v.x; s[1] += v.y; s[2] += v.z; s[3] += v.w;
            }
#pragma unroll
            for (int e = 0; e < 4; e++) cx.cs[T][e] = s[e];
            bar_sync(1);
        }
        const char* xp = cx.grp + cx.h * 16384 + 8192 + (1 - cx.gside) * 4096 + w * 512 + ((g & 1) * 4 + t) * 16;
        uint4 x[4];
        do {
#pragma unroll
            for (int i = 0; i < 4; i++) x[i] = ld_pkt(xp + i * 128);
        } while (x[0].z != tag || x[1].z != tag || x[2].z != tag || x[3].z != tag);
        __syncwarp();
        TL(1);
        sideO = (t & 2) ? ((t & 1) ? x[3].w : x[2].w) : ((t & 1) ? x[1].w : x[0].w);
        float a[2][2][4], st[2][4];
#pragma unroll
        for (int u = 0; u < 2; u++)
#pragma unroll
            for (int e = 0; e < 4; e++) a[u][0][e] = a[u][1][e] = st[u][e] = 0.f;
#pragma unroll
        for (int i = 0; i < 4; i++) {
            mma(a[i >> 1][0], wf[i][0], x[i].x, x[i].y);
            mma(a[i >> 1][1], wf[i][1], x[i].x, x[i].y);
            mma(st[i >> 1], x[i].x, kOnes, x[i].y, kOnes, x[i].x, x[i].y);
        }
        qp[qpw] = pick4(a[0][0], t) + pick4(a[1][0], t);
        qp[qpw + 32] = pick4(a[0][1], t) + pick4(a[1][1], t);
        if (t == 0 && g < 2) {
            const float sum = g ? st[0][3] + st[1][3] : st[0][2] + st[1][2];
            const float sq = g ? st[0][1] + st[1][1] : st[0][0] + st[1][0];
            *reinterpret_cast<float2*>(cx.sm + SM_ST + g * 64 + w * 8) = make_float2(sum, sq);
        }
        if (w == 0) {
            bar_sync(2);
            float s[4] = {0.f, 0.f, 0.f, 0.f};
#pragma unroll
            for (int i = 0; i < 8; i++) {
                const float4 v = *reinterpret_cast<const float4*>(qp + i * 64 + qpr);
                s[0] += v.x; s[1] += v.y; s[2] += v.z; s[3] += v.w;
            }
            float sum = 0.f, sq = 0.f;
#pragma unroll
            for (int i = 0; i < 4; i++) {
                const float4 v = *reinterpret_cast<const float4*>(cx.sm + SM_ST + ((lane >> 3) & 1) * 64 + i * 16);
                sum += v.x + v.z;
                sq += v.y + v.w;
            }
            const float mean = sum * (1.f / 512.f);
            const float var = fmaxf(fmaf(-mean, mean, sq * (1.f / 512.f)), 0.f);
            const float rstd = rsqrtf(var + 1e-5f);
            float q[4];
#pragma unroll
            for (int e = 0; e < 4; e++) q[e] = rstd * fmaf(-mean, cx.cs[T][e], s[e]);
            st_pkt(cx.grp + cx.h * 16384 + (lane >> 4) * 4096 + cx.c * 256 + (lane & 15) * 16,
                   pack_bf16(q[0], q[1]), pack_bf16(q[2], q[3]), tag, cx.side);
        } else {
            bar_arrive(2);
        }
        TL(2);
    }

    uint32_t qf[16];
    {
        const char* qsrc = cx.grp + cx.h * 16384 + cx.gside * 4096 + tid * 16;
        uint4 v;
        do {
            v = ld_pkt(qsrc);
        } while (v.z != tag);
        __syncwarp();
        sideD = v.w;
        const int src = tid >> 4, j = tid & 15;
        *reinterpret_cast<uint2*>(cx.sm + SM_Q + (src & 3) * 512 + (((j >> 3) * 4 + (src >> 2)) * 4 + (j & 3)) * 16 +
                                  ((j >> 2) & 1) * 8) = make_uint2(v.x, v.y);
        bar_sync(1);
        TL(3);
#pragma unroll
        for (int i = 0; i < 4; i++) {
            const uint4 u = *reinterpret_cast<const uint4*>(cx.sm + SM_Q + i * 512 + lane * 16);
            qf[4 * i] = u.x; qf[4 * i + 1] = u.y; qf[4 * i + 2] = u.z; qf[4 * i + 3] = u.w;
        }
    }

    {
        float s[2][4];
#pragma unroll
        for (int e = 0; e < 4; e++) s[0][e] = s[1][e] = 0.f;
        if (actS) {
            float b[2][4];
#pragma unroll
            for (int e = 0; e < 4; e++) b[0][e] = b[1][e] = 0.f;
#pragma unroll
            for (int j = 0; j < 8; j += 2) {
                mma(s[0], &bank[j * 4], qf[2 * j], qf[2 * j + 1]);
                mma(s[1], &bank[32 + j * 4], qf[2 * j], qf[2 * j + 1]);
                mma(b[0], &bank[j * 4 + 4], qf[2 * j + 2], qf[2 * j + 3]);
                mma(b[1], &bank[32 + j * 4 + 4], qf[2 * j + 2], qf[2 * j + 3]);
            }
#pragma unroll
            for (int e = 0; e < 4; e++) { s[0][e] += b[0][e]; s[1][e] += b[1][e]; }
        }
        if (actF) {
            mbar_wait(cx.sb + BAR_FULLK + w * 8, p & 1);
            const uint32_t ka = cx.sb + SM_K + w * kTile + (mi & 1) * 2048 + r * 128 + (((mi >> 1) ^ r) << 4);
            float f[2][4];
#pragma unroll
            for (int e = 0; e < 4; e++) f[0][e] = f[1][e] = 0.f;
#pragma unroll
            for (int j = 0; j < 8; j++) {
                const uint32_t aj = (ka ^ ((j & 3) << 5)) + (j >> 2) * 1024;
                ldsm4(&bank[j * 4], aj);
                ldsm4(&bank[32 + j * 4], aj + 4096);
            }
#pragma unroll
            for (int j = 0; j < 8; j++) {
                mma(f[0], &bank[j * 4], qf[2 * j], qf[2 * j + 1]);
                mma(f[1], &bank[32 + j * 4], qf[2 * j], qf[2 * j + 1]);
            }
            if ((t >> 1) == slotF) {
#pragma unroll
                for (int e = 0; e < 4; e++) { s[0][e] = f[0][e]; s[1][e] = f[1][e]; }
            }
            if (actS) {
                asm volatile("" ::"f"(f[0][0]), "f"(f[1][0]) : "memory");
                __syncwarp();
                if (lane == 0) {
                    const uint32_t bar = cx.sb + BAR_FULLR + (w >> 1) * 8;
                    mbar_expect(bar, kTile);
                    tma_kv(cx.sb + SM_K + w * kTile, &maps.v[T], (((p >> 1) - 1) * 8 + cx.h) * 512 + cx.c * 32 + w * 4, bar,
                           policy_first());
                }
            }
        }
        TL(4);
        float m0 = fmaxf(fmaxf(s[0][0], s[0][2]), fmaxf(s[1][0], s[1][2]));
        float m1 = fmaxf(fmaxf(s[0][1], s[0][3]), fmaxf(s[1][1], s[1][3]));
#pragma unroll
        for (int d = 4; d < 32; d <<= 1) {
            m0 = fmaxf(m0, __shfl_xor_sync(0xffffffffu, m0, d));
            m1 = fmaxf(m1, __shfl_xor_sync(0xffffffffu, m1, d));
        }
        m0 *= kScale;
        m1 *= kScale;
        uint32_t pk[4];
#pragma unroll
        for (int u = 0; u < 2; u++) {
            pk[2 * u] = movm(pack_bf16(ex2(fmaf(s[u][0], kScale, -m0)), ex2(fmaf(s[u][1], kScale, -m1))));
            pk[2 * u + 1] = movm(pack_bf16(ex2(fmaf(s[u][2], kScale, -m0)), ex2(fmaf(s[u][3], kScale, -m1))));
        }
        *reinterpret_cast<uint4*>(cx.sm + SM_P + w * 512 + lane * 16) = make_uint4(pk[0], pk[1], pk[2], pk[3]);
        if (g == 0) *reinterpret_cast<float2*>(cx.sm + SM_M + t * 64 + w * 8) = make_float2(m0, m1);
        bar_sync(1);
        TL(5);
    }

    {
        if (!actS && lane < 4) mbar_arrive(cx.sb + BAR_EMPTYK + lane * 8);
        float m0 = -INFINITY, m1 = -INFINITY;
#pragma unroll
        for (int i = 0; i < 4; i++) {
            const float4 v = *reinterpret_cast<const float4*>(cx.sm + SM_M + t * 64 + i * 16);
            m0 = fmaxf(m0, fmaxf(v.x, v.z));
            m1 = fmaxf(m1, fmaxf(v.y, v.w));
        }
        const int ch = 2 * w + (mi & 1);
        const uint32_t voff = (mi >> 1) * 2048 + (ch >> 3) * 1024 + r * 128 + (((ch & 7) ^ r) << 4);
        float acc[4] = {0.f, 0.f, 0.f, 0.f}, ls[2] = {0.f, 0.f};
        auto firstTile = [&](int i) {
            mbar_wait(cx.sb + BAR_FULLV + cx.vslot * 8, cx.vpar);
            pv_tile(cx, cx.sb + SM_V + cx.vslot * kTile + voff, i, slotF, m0, m1, acc, ls);
            __syncwarp();
            if (lane == 0) mbar_arrive(cx.sb + BAR_EMPTYV + cx.vslot * 8);
            if (++cx.vslot == kNV) { cx.vslot = 0; cx.vpar ^= 1; }
        };
        auto secondPair = [&](int i) {
            mbar_wait(cx.sb + BAR_FULLR + i * 8, p & 1);
            pv_tile(cx, cx.sb + SM_K + (2 * i) * kTile + voff, 2 * i, slotS, m0, m1, acc, ls);
            pv_tile(cx, cx.sb + SM_K + (2 * i + 1) * kTile + voff, 2 * i + 1, slotS, m0, m1, acc, ls);
            __syncwarp();
            if (lane == 0) mbar_arrive(cx.sb + BAR_EMPTYK + i * 8);
        };
        if (actF) {
#pragma unroll 1
            for (int i = 0; i < kNV; i++) firstTile(i);
        }
        TL(6);
        if (actS) {
#pragma unroll
            for (int i = 0; i < 4; i++) secondPair(i);
        }
        TL(7);
        if (actF) {
#pragma unroll 1
            for (int i = kNV; i < 8; i++) firstTile(i);
        }
        TL(8);
        const int slot = t >> 1;
        if (slot == slotF ? actF : actS) {
            const float r0 = __fdividef(1.f, ls[0]), r1 = __fdividef(1.f, ls[1]);
            const float e0 = m0 + __log2f(ls[0]), e1 = m1 + __log2f(ls[1]);
            const int dst = cx.h * 16 + (tid >> 4);
            st_pkt(cx.box + (dst >> 2) * 65536 + (dst & 3) * 16384 + sideD * 4096 + cx.c * 256 + slot * 128 +
                       ((g & 3) * 2 + (t & 1)) * 16,
                   pack_bf16(acc[0] * r0, acc[1] * r1), pack_bf16(acc[2] * r0, acc[3] * r1), __float_as_uint(e0),
                   (__float_as_uint(e1) & ~31u) | tag);
        }
    }

    {
        if (p < 2) {
            mbar_wait(cx.sb + BAR_FULLW + (4 * T + 2) * 8, 0);
            mbar_wait(cx.sb + BAR_FULLW + (4 * T + 3) * 8, 0);
        }
        uint32_t wf[4][2][4];
        const uint32_t wa = cx.sb + SM_WO + T * 32 * kWoPitch + ((mi >> 1) * 8 + r) * kWoPitch + (64 * w + (mi & 1) * 8) * 2;
#pragma unroll
        for (int i = 0; i < 4; i++) {
            ldsm4t(wf[i][0], wa + i * 32);
            ldsm4t(wf[i][1], wa + i * 32 + 16 * kWoPitch);
        }
        if (w < 2) {
            uint2 res = make_uint2(0, 0);
            if (w == slotF ? actF : actS) {
                const char* src = cx.box + (cta >> 2) * 65536 + (cta & 3) * 16384 + cx.side * 4096 + (lane >> 3) * 256 +
                                  w * 128 + (lane & 7) * 16;
                uint4 v[4];
                do {
#pragma unroll
                    for (int i = 0; i < 4; i++) v[i] = ld_pkt(src + i * 1024);
                } while ((((v[0].w ^ tag) | (v[1].w ^ tag) | (v[2].w ^ tag) | (v[3].w ^ tag)) & 31u) != 0);
                __syncwarp();
                TL(9);
                float e0[4], e1[4];
#pragma unroll
                for (int i = 0; i < 4; i++) {
                    e0[i] = __uint_as_float(v[i].z);
                    e1[i] = __uint_as_float(v[i].w & ~31u);
                }
                float m0 = fmaxf(fmaxf(e0[0], e0[1]), fmaxf(e0[2], e0[3]));
                float m1 = fmaxf(fmaxf(e1[0], e1[1]), fmaxf(e1[2], e1[3]));
#pragma unroll
                for (int d = 8; d < 32; d <<= 1) {
                    m0 = fmaxf(m0, __shfl_xor_sync(0xffffffffu, m0, d));
                    m1 = fmaxf(m1, __shfl_xor_sync(0xffffffffu, m1, d));
                }
                float o[4] = {0.f, 0.f, 0.f, 0.f}, w0 = 0.f, w1 = 0.f;
#pragma unroll
                for (int i = 0; i < 4; i++) {
                    const float a = ex2(e0[i] - m0), b = ex2(e1[i] - m1);
                    w0 += a;
                    w1 += b;
                    o[0] = fmaf(a, bf_lo(v[i].x), o[0]);
                    o[1] = fmaf(b, bf_hi(v[i].x), o[1]);
                    o[2] = fmaf(a, bf_lo(v[i].y), o[2]);
                    o[3] = fmaf(b, bf_hi(v[i].y), o[3]);
                }
#pragma unroll
                for (int d = 8; d < 32; d <<= 1) {
                    w0 += __shfl_xor_sync(0xffffffffu, w0, d);
                    w1 += __shfl_xor_sync(0xffffffffu, w1, d);
#pragma unroll
                    for (int e = 0; e < 4; e++) o[e] += __shfl_xor_sync(0xffffffffu, o[e], d);
                }
                const float r0 = __fdividef(1.f, w0), r1 = __fdividef(1.f, w1);
                res = make_uint2(pack_bf16(o[0] * r0, o[1] * r1), pack_bf16(o[2] * r0, o[3] * r1));
            }
            if (lane < 8) *reinterpret_cast<uint2*>(cx.sm + SM_O + w * 64 + lane * 8) = res;
        }
        bar_sync(1);
        TL(10);
        const uint4 ob = *reinterpret_cast<const uint4*>(cx.sm + SM_O + (g & 1) * 64 + t * 16);
        float y[4][4];
#pragma unroll
        for (int i = 0; i < 4; i++) {
#pragma unroll
            for (int e = 0; e < 4; e++) y[i][e] = 0.f;
            mma(y[i], wf[i][0], ob.x, ob.y);
            mma(y[i], wf[i][1], ob.z, ob.w);
        }
        float z[4];
#pragma unroll
        for (int e = 0; e < 4; e++) {
            const float a = (t & 1) ? y[1][e] : y[0][e];
            const float b = (t & 1) ? y[3][e] : y[2][e];
            z[e] = (t & 2) ? b : a;
        }
        st_pkt(cx.box + (4 * w + t) * 65536 + (cta >> 5) * 16384 + (3 - sideO) * 4096 + (cta & 31) * 128 + g * 16,
               (__float_as_uint(z[0]) & ~31u) | tag, __float_as_uint(z[1]), __float_as_uint(z[2]), __float_as_uint(z[3]));
        TL(11);
    }

    if (owner) {
        const char* src = cx.box + (cta >> 2) * 65536 + (3 - cx.side) * 4096 + tid * 16;
        uint4 v[4];
        do {
#pragma unroll
            for (int i = 0; i < 4; i++) v[i] = ld_pkt(src + i * 16384);
        } while ((((v[0].x ^ tag) | (v[1].x ^ tag) | (v[2].x ^ tag) | (v[3].x ^ tag)) & 31u) != 0);
        __syncwarp();
        TL(12);
        float z[4];
        z[0] = (__uint_as_float(v[0].x & ~31u) + __uint_as_float(v[1].x & ~31u)) +
               (__uint_as_float(v[2].x & ~31u) + __uint_as_float(v[3].x & ~31u));
        z[1] = (__uint_as_float(v[0].y) + __uint_as_float(v[1].y)) + (__uint_as_float(v[2].y) + __uint_as_float(v[3].y));
        z[2] = (__uint_as_float(v[0].z) + __uint_as_float(v[1].z)) + (__uint_as_float(v[2].z) + __uint_as_float(v[3].z));
        z[3] = (__uint_as_float(v[0].w) + __uint_as_float(v[1].w)) + (__uint_as_float(v[2].w) + __uint_as_float(v[3].w));
#pragma unroll
        for (int d = 8; d < 32; d <<= 1)
#pragma unroll
            for (int e = 0; e < 4; e++) z[e] += __shfl_xor_sync(0xffffffffu, z[e], d);
        float* red = reinterpret_cast<float*>(cx.sm + SM_R);
        red[w * 32 + (mi & 1) * 16 + (r >> 1) * 4 + (mi & 2) + (r & 1)] = pick4(z, mi);
        if (w < 4) {
            bar_sync(3);
            float s[4] = {0.f, 0.f, 0.f, 0.f};
#pragma unroll
            for (int i = 0; i < 8; i++) {
                const float4 u = *reinterpret_cast<const float4*>(red + i * 32 + r * 4);
                s[0] += u.x; s[1] += u.y; s[2] += u.z; s[3] += u.w;
            }
            const uint32_t ya = pack_bf16(s[0], s[1]), yb = pack_bf16(s[2], s[3]);
            cx.xa = pack_bf16(bf_lo(cx.xa) + bf_lo(ya), bf_hi(cx.xa) + bf_hi(ya));
            cx.xb = pack_bf16(bf_lo(cx.xb) + bf_lo(yb), bf_hi(cx.xb) + bf_hi(yb));
            if (T == 1 && (r >> 2) == slotS) {
                if (actS && tid < 8) {
                    uint32_t* dst = reinterpret_cast<uint32_t*>(cx.out + ((p >> 1) - 1) * 512 + (cta >> 2) * 16);
                    dst[t] = cx.xa;
                    dst[4 + t] = cx.xb;
                }
                cx.xa = nxa;
                cx.xb = nxb;
            }
            if (p + 1 < kPhases) send_x(cx, tag + 1);
        } else {
            bar_arrive(3);
        }
        TL(13);
    }
}

__device__ __forceinline__ void producer(const Maps& maps, const __nv_bfloat16* woA, const __nv_bfloat16* woB,
                                         uint32_t sb, int h, int c, int lane) {
    const uint64_t polF = policy_first(), polN = policy_normal();
#pragma unroll 1
    for (int u = 0; u < 8; u++) {
        const uint32_t bar = sb + BAR_FULLW + u * 8;
        const int T = u >> 2, half = u & 1;
        if (u >= 2) mbar_wait(bar - 16, 0);
        if (lane == 0) mbar_expect(bar, 16384);
        __syncwarp();
        if ((u & 2) == 0) {
            if (lane == 0) tma_2d(sb + SM_WQ + T * 32768 + half * 16384, &maps.wq[T], h * 512 + c * 32, half * 256, bar, polF);
        } else if (lane < 16) {
            const int row = half * 16 + lane;
            const int grow = h * 512 + (2 * half + (row & 1)) * 128 + 16 * (c >> 1) + 8 * ((row >> 3) & 1) + 4 * (c & 1) +
                             ((row >> 1) & 3);
            bulk_1d(sb + SM_WO + (T * 32 + row) * kWoPitch, (T ? woB : woA) + (size_t)grow * 512, 1024, bar, polF);
        }
    }
    if (lane != 0) return;
    int vs = 0, ws = 0;
    uint32_t vpar = 1, wpar = 0;
#pragma unroll 1
    for (int p = 0; p < 16; p++) {
        const int T = p & 1;
        const int g0 = ((p >> 1) * 8 + h) * 512 + c * 32;
#pragma unroll
        for (int i = 0; i < 16; i++) {
            const int j = i - kWin;
            if (j >= 0 && j < 8) {
                mbar_wait(sb + BAR_FULLK + j * 8, p & 1);
            } else if (j < 0 && p == 0) {
                if (i == 0) mbar_wait(sb + BAR_FULLW + 6 * 8, 0);
                if (i == 2) mbar_wait(sb + BAR_FULLW + 7 * 8, 0);
            } else {
                const int vj = (j + 16) & 7;
                const int issuedAfter = (j < 0 ? 8 : i - 8) - vj;
                if (issuedAfter <= kNV) mbar_wait(sb + BAR_FULLV + ws * 8, wpar);
                if (++ws == kNV) { ws = 0; wpar ^= 1; }
            }
            if (i < 8) {
                if (p > 0 && (i & 1) == 0) mbar_wait(sb + BAR_EMPTYK + (i >> 1) * 8, (p - 1) & 1);
                mbar_expect(sb + BAR_FULLK + i * 8, kTile);
                tma_kv(sb + SM_K + i * kTile, &maps.k[T], g0 + i * 4, sb + BAR_FULLK + i * 8, polF);
            } else {
                mbar_wait(sb + BAR_EMPTYV + vs * 8, vpar);
                mbar_expect(sb + BAR_FULLV + vs * 8, kTile);
                tma_kv(sb + SM_V + vs * kTile, &maps.v[T], g0 + (i - 8) * 4, sb + BAR_FULLV + vs * 8, polN);
                if (++vs == kNV) { vs = 0; vpar ^= 1; }
            }
        }
    }
#pragma unroll 1
    for (int p = 16; p < kPhases; p++) {
        const int g0 = (7 * 8 + h) * 512 + c * 32;
#pragma unroll
        for (int i = 0; i < 8; i++) {
            const uint32_t bar = sb + BAR_FULLR + (i >> 1) * 8;
            if ((i & 1) == 0) mbar_wait(sb + BAR_EMPTYK + (i >> 1) * 8, (p - 1) & 1);
            mbar_expect(bar, kTile);
            tma_kv(sb + SM_K + i * kTile, &maps.v[p & 1], g0 + i * 4, bar, polF);
        }
    }
}

__global__ void __launch_bounds__(kThreads, 1)
decode_kernel(const __grid_constant__ Maps maps, const __nv_bfloat16* __restrict__ x0,
              const __nv_bfloat16* __restrict__ woA, const __nv_bfloat16* __restrict__ woB,
              __nv_bfloat16* __restrict__ out) {
    extern __shared__ __align__(1024) char smem[];
    const uint32_t sb = (uint32_t)__cvta_generic_to_shared(smem);
    const int tid = threadIdx.x, w = tid >> 5, lane = tid & 31;
    const int cta = blockIdx.x, h = cta >> 4, c = cta & 15;

    if (w >= 8) {
        asm volatile("setmaxnreg.dec.sync.aligned.u32 40;");
        if (w > 9) return;
        if (w == 9) {
            asm volatile("bar.sync 4, 320;" ::: "memory");
            if (lane == 0) {
                const long long t0 = clock64();
                while (!mbar_try(sb + BAR_DONE, 0))
                    if (clock64() - t0 > kWatchdogClocks) asm volatile("st.volatile.global.u32 [%0], 0;" ::"l"(0ull) : "memory");
            }
            return;
        }
        if (lane == 31) mbar_init(sb + BAR_DONE, 8);
        if (lane < 8) {
            mbar_init(sb + BAR_FULLK + lane * 8, 1);
            mbar_init(sb + BAR_FULLW + lane * 8, 1);
        } else if (lane < 12) {
            mbar_init(sb + BAR_FULLR + (lane - 8) * 8, 2);
            mbar_init(sb + BAR_EMPTYK + (lane - 8) * 8, 8);
        } else if (lane < 12 + kNV) {
            mbar_init(sb + BAR_FULLV + (lane - 12) * 8, 1);
            mbar_init(sb + BAR_EMPTYV + (lane - 12) * 8, 8);
        }
        asm volatile("fence.mbarrier_init.release.cluster;" ::: "memory");
        __syncwarp();
        asm volatile("bar.arrive 4, 320;" ::: "memory");
        producer(maps, woA, woB, sb, h, c, lane);
        return;
    }

    asm volatile("setmaxnreg.inc.sync.aligned.u32 232;");
    Ctx cx;
    cx.sm = smem;
    cx.sb = sb;
    cx.box = reinterpret_cast<char*>((reinterpret_cast<uintptr_t>(g_scratch) + 65535) & ~(uintptr_t)65535);
    cx.grp = cx.box + kBoxBytes;
    cx.x0 = x0;
    cx.out = out;
    cx.h = h; cx.c = c; cx.w = w; cx.lane = lane;
    cx.vslot = 0;
    cx.vpar = 0;
    cx.xa = cx.xb = 0;
    if ((c & 3) == 0 && w < 4 && (lane & 4) == 0) {
        const uint32_t* src = reinterpret_cast<const uint32_t*>(x0 + (cta >> 2) * 16);
        cx.xa = __ldg(src + (lane & 3));
        cx.xb = __ldg(src + 4 + (lane & 3));
    }

    if (w < 4 && lane == 0) {
        char* pa = (w < 2) ? cx.box + (cta >> 2) * 65536 + (cta & 3) * 16384 + w * 4096 + c * 256
                           : cx.grp + h * 16384 + (w - 2) * 4096 + c * 256;
        st_pkt(pa, 0, 0, 0, 0);
        st_pkt(pa + 16, 0, 0, 0, 0);
        uint32_t best = 0xffffffffu;
#pragma unroll 1
        for (int i = 0; i < 4; i++) {
            uint32_t t0, t1, old;
            asm volatile("mov.u32 %0, %%clock;" : "=r"(t0)::"memory");
            asm volatile("atom.relaxed.gpu.global.exch.b32 %0, [%1], %2;" : "=r"(old) : "l"(pa), "r"(i) : "memory");
            asm volatile("{.reg .pred p; setp.eq.u32 p, %1, -1; @p exit; mov.u32 %0, %%clock;}" : "=r"(t1) : "r"(old) : "memory");
            best = min(best, t1 - t0);
        }
        reinterpret_cast<uint32_t*>(smem + SM_PR)[w] = best;
    }
    asm volatile("bar.sync 4, 320;" ::: "memory");
    {
        const uint4 pr = *reinterpret_cast<const uint4*>(smem + SM_PR);
        cx.side = pr.y < pr.x;
        cx.gside = pr.w < pr.z;
    }
    if ((c & 3) == 0 && w < 4) send_x(cx, 1);

    uint32_t bankA[64], bankB[64];
#pragma unroll
    for (int i = 0; i < 64; i++) bankA[i] = bankB[i] = 0;
#pragma unroll 1
    for (int p = 0; p < kPhases; p += 2) {
        phase<0>(cx, maps, p, bankA);
        phase<1>(cx, maps, p + 1, bankB);
    }
    if (lane == 0) mbar_arrive(sb + BAR_DONE);
}

typedef CUresult (*EncodeFn)(CUtensorMap*, CUtensorMapDataType, cuuint32_t, void*, const cuuint64_t*, const cuuint64_t*,
                             const cuuint32_t*, const cuuint32_t*, CUtensorMapInterleave, CUtensorMapSwizzle,
                             CUtensorMapL2promotion, CUtensorMapFloatOOBfill);

void encode_kv(EncodeFn fn, CUtensorMap* m, void* base) {
    const cuuint64_t dims[4] = {64, 8, 2, 32768};
    const cuuint64_t strides[3] = {256, 128, 2048};
    const cuuint32_t box[4] = {64, 8, 2, 4};
    const cuuint32_t es[4] = {1, 1, 1, 1};
    fn(m, CU_TENSOR_MAP_DATA_TYPE_BFLOAT16, 4, base, dims, strides, box, es, CU_TENSOR_MAP_INTERLEAVE_NONE,
       CU_TENSOR_MAP_SWIZZLE_128B, CU_TENSOR_MAP_L2_PROMOTION_NONE, CU_TENSOR_MAP_FLOAT_OOB_FILL_NONE);
}

void encode_wq(EncodeFn fn, CUtensorMap* m, void* base) {
    const cuuint64_t dims[2] = {4096, 512};
    const cuuint64_t strides[1] = {8192};
    const cuuint32_t box[2] = {32, 256};
    const cuuint32_t es[2] = {1, 1};
    fn(m, CU_TENSOR_MAP_DATA_TYPE_BFLOAT16, 2, base, dims, strides, box, es, CU_TENSOR_MAP_INTERLEAVE_NONE,
       CU_TENSOR_MAP_SWIZZLE_64B, CU_TENSOR_MAP_L2_PROMOTION_NONE, CU_TENSOR_MAP_FLOAT_OOB_FILL_NONE);
}

}

extern "C" void kernel_launch(void* const* d_in, const int* in_sizes, int n_in, void* d_out, int out_size) {
    static EncodeFn encode = nullptr;
    if (!encode) {
        void* fn = nullptr;
        cudaDriverEntryPointQueryResult st;
        cudaGetDriverEntryPoint("cuTensorMapEncodeTiled", &fn, cudaEnableDefault, &st);
        encode = reinterpret_cast<EncodeFn>(fn);
        cudaFuncSetAttribute(decode_kernel, cudaFuncAttributeMaxDynamicSharedMemorySize, SM_TOTAL);
    }
    Maps maps;
    encode_kv(encode, &maps.k[0], d_in[1]);
    encode_kv(encode, &maps.v[0], d_in[2]);
    encode_kv(encode, &maps.k[1], d_in[6]);
    encode_kv(encode, &maps.v[1], d_in[7]);
    encode_wq(encode, &maps.wq[0], d_in[3]);
    encode_wq(encode, &maps.wq[1], d_in[8]);
    decode_kernel<<<kCtas, kThreads, SM_TOTAL>>>(maps, static_cast<const __nv_bfloat16*>(d_in[0]),
                                                 static_cast<const __nv_bfloat16*>(d_in[4]),
                                                 static_cast<const __nv_bfloat16*>(d_in[9]),
                                                 static_cast<__nv_bfloat16*>(d_out));
}
```

```cpp
#include <cuda_runtime.h>
#include <cuda_bf16.h>
#include <cuda.h>
#include <stdint.h>
#include <limits.h>

namespace {

#define RES 1
#define WIN 4
#define AHEAD 12
#define TRASHMASK 0x0800
#define NREQ 1
#define WMAX 5
#define SCHA 2500
#define SCHB 550
#define WWIN 2
#define WIN0 4
#define EARLY 2
#define OWNLATE 0
#define OWNWQ 0
#define RGAPA 300
#define SPAN 7
#define WMASK 0xe000
#define WMASK2 0
#define WNEG 0
#define NPROBE 16
#define NSH 2
#define SCA0 0
#define SCB0 630
#define WMAX0 6
#define WORDER 0
#define WQW 0
#define NEARCLK 410
#define T20 16500
#define PARKMASK 0xffff
#define RGAPB 400
#define TRASH 2048
#define RGATE 4
#define RGAP 800
#define DLY1 170
#define DLY2 280
#define DLY3 1400
#define DLY3O 220
#define DLY4 0

constexpr int kCtas = 128;
constexpr int kThreads = 384;
constexpr int kPhases = 18;
constexpr int kTile = 8192;
constexpr int kRes = RES;
constexpr int kX = 2 * kRes - 1;
constexpr int kWin = WIN;
constexpr int kWinMax = WMAX;
constexpr int kEarly = EARLY;
constexpr int kWoPitch = 1040;
constexpr uint32_t kSpinLimit = 1u << 22;
constexpr float kScale = 0.08838834764831845f * 1.4426950408889634f;
constexpr uint32_t kOnes = 0x3f803f80u;

constexpr int SM_K = 0;
constexpr int SM_V = SM_K + 8 * kTile;
constexpr int SM_R = SM_V + kX * kTile;
constexpr int SM_RB = SM_K + kX * kTile;
constexpr int SM_P = SM_R + 4 * kTile;
constexpr int SM_RED = SM_P;
constexpr int SM_QP = SM_P + 1024;
constexpr int SM_WQ = SM_P + 4096;
constexpr int SM_WOB = SM_WQ + 2 * 32768;
constexpr int SM_WOA = SM_WOB + 32 * kWoPitch;
constexpr int SM_Q = SM_WOA + (2 - kRes) * 16 * kWoPitch;
constexpr int SM_ST = SM_Q + 2048;
constexpr int SM_M = SM_ST + 128;
constexpr int SM_SC = SM_M + 128;
constexpr int SM_O = SM_SC + 64;
constexpr int SM_CS = SM_O + 128;
constexpr int SM_X0 = SM_CS + 256;
constexpr int SM_PR = SM_X0 + 256;
constexpr int SM_T2 = SM_PR + 32;
constexpr int SM_HS = SM_T2 + 16;
constexpr int SM_BAR = SM_HS + 64;
constexpr int BAR_FULL = SM_BAR;
constexpr int BAR_EMPTY = BAR_FULL + 16 * 8;
constexpr int BAR_EMPTYR = BAR_EMPTY + 16 * 8;
constexpr int BAR_FULLR = BAR_EMPTYR + 6 * 8;
constexpr int BAR_FULLW = BAR_FULLR + 6 * 8;
constexpr int BAR_DONE = BAR_FULLW + 16 * 8;
constexpr int SM_TL = BAR_DONE + 8;
constexpr int SM_TOTAL = SM_TL;
static_assert(SM_TOTAL <= 232448, "shared memory budget");

constexpr uint32_t kBoxBytes = 32 * 65536;
constexpr uint32_t kGrpBytes = 8 * 16384;
constexpr uint32_t kSideTable = kBoxBytes + kGrpBytes;
__device__ uint4 g_scratch[(kSideTable + 4096 + 65536) / 16];

#define TL(i)
#define TLW(i)
#define GT(i)

struct Params {
    CUtensorMap kv[4];
    CUtensorMap wq[2];
    const char* kvp[4];
    const __nv_bfloat16* wo[2];
    const __nv_bfloat16* x0;
    __nv_bfloat16* out;
};

__device__ __forceinline__ void fault() { asm volatile("st.volatile.global.u32 [%0], 0;" ::"l"(0ull) : "memory"); }
__device__ __forceinline__ void mbar_init(uint32_t a, uint32_t c) {
    asm volatile("mbarrier.init.shared::cta.b64 [%0], %1;" ::"r"(a), "r"(c) : "memory");
}
__device__ __forceinline__ void mbar_expect(uint32_t a, uint32_t bytes) {
    asm volatile("mbarrier.arrive.expect_tx.shared::cta.b64 _, [%0], %1;" ::"r"(a), "r"(bytes) : "memory");
}
__device__ __forceinline__ void mbar_arrive(uint32_t a) {
    asm volatile("mbarrier.arrive.shared::cta.b64 _, [%0];" ::"r"(a) : "memory");
}
__device__ __forceinline__ uint32_t mbar_try(uint32_t a, uint32_t parity) {
    uint32_t ok;
    asm volatile("{.reg .pred p; mbarrier.try_wait.parity.shared::cta.b64 p, [%1], %2; selp.u32 %0, 1, 0, p;}"
                 : "=r"(ok) : "r"(a), "r"(parity) : "memory");
    return ok;
}
__device__ __forceinline__ uint32_t mbar_test(uint32_t a, uint32_t parity) {
    uint32_t ok;
    asm volatile("{.reg .pred p; mbarrier.test_wait.parity.shared::cta.b64 p, [%1], %2; selp.u32 %0, 1, 0, p;}"
                 : "=r"(ok) : "r"(a), "r"(parity) : "memory");
    return ok;
}
__device__ __forceinline__ void mbar_wait(uint32_t a, uint32_t parity) {
    while (!mbar_try(a, parity)) {}
}
__device__ __forceinline__ void tma_kv(uint32_t dst, const CUtensorMap* m, int group, uint32_t bar, uint64_t pol) {
    asm volatile("cp.async.bulk.tensor.4d.shared::cluster.global.mbarrier::complete_tx::bytes.L2::cache_hint"
                 " [%0], [%1, {%3, %3, %3, %4}], [%2], %5;"
                 ::"r"(dst), "l"(m), "r"(bar), "r"(0), "r"(group), "l"(pol) : "memory");
}
__device__ __forceinline__ void tma_2d(uint32_t dst, const CUtensorMap* m, int x, int y, uint32_t bar, uint64_t pol) {
    asm volatile("cp.async.bulk.tensor.2d.shared::cluster.global.mbarrier::complete_tx::bytes.L2::cache_hint"
                 " [%0], [%1, {%3, %4}], [%2], %5;"
                 ::"r"(dst), "l"(m), "r"(bar), "r"(x), "r"(y), "l"(pol) : "memory");
}
__device__ __forceinline__ void bulk_1d(uint32_t dst, const void* src, uint32_t bytes, uint32_t bar, uint64_t pol) {
    asm volatile("cp.async.bulk.shared::cluster.global.mbarrier::complete_tx::bytes.L2::cache_hint"
                 " [%0], [%1], %2, [%3], %4;"
                 ::"r"(dst), "l"(src), "r"(bytes), "r"(bar), "l"(pol) : "memory");
}
__device__ __forceinline__ void prefetch_l2(const void* src, uint32_t bytes, uint64_t pol) {
    asm volatile("cp.async.bulk.prefetch.L2.global.L2::cache_hint [%0], %1, %2;" ::"l"(src), "r"(bytes), "l"(pol) : "memory");
}
__device__ __forceinline__ bool elect_one() {
    uint32_t pred;
    asm volatile("{.reg .pred p; elect.sync _|p, 0xffffffff; selp.u32 %0, 1, 0, p;}" : "=r"(pred));
    return pred;
}
__device__ __forceinline__ uint32_t clock32() {
    uint32_t c;
    asm volatile("mov.u32 %0, %%clock;" : "=r"(c)::"memory");
    return c;
}
__device__ __forceinline__ void wait_until(uint32_t t0, uint32_t n) {
    while (clock32() - t0 < n) {}
}
__device__ __forceinline__ uint64_t policy_first() {
    uint64_t p;
    asm volatile("createpolicy.fractional.L2::evict_first.b64 %0, 1.0;" : "=l"(p));
    return p;
}
__device__ __forceinline__ uint64_t policy_normal() {
    uint64_t p;
    asm volatile("createpolicy.fractional.L2::evict_normal.b64 %0, 1.0;" : "=l"(p));
    return p;
}
__device__ __forceinline__ void st_pkt(char* p, uint32_t a, uint32_t b, uint32_t c, uint32_t d) {
    asm volatile("{.reg .b128 r; .reg .b64 lo, hi; mov.b64 lo, {%1, %2}; mov.b64 hi, {%3, %4}; mov.b128 r, {lo, hi};"
                 " st.relaxed.gpu.global.b128 [%0], r;}"
                 ::"l"(p), "r"(a), "r"(b), "r"(c), "r"(d) : "memory");
}
__device__ __forceinline__ uint4 ld_pkt(const char* p) {
    uint4 v;
    asm volatile("{.reg .b128 r; .reg .b64 lo, hi; ld.relaxed.gpu.global.b128 r, [%4]; mov.b128 {lo, hi}, r;"
                 " mov.b64 {%0, %1}, lo; mov.b64 {%2, %3}, hi;}"
                 : "=r"(v.x), "=r"(v.y), "=r"(v.z), "=r"(v.w) : "l"(p) : "memory");
    return v;
}
__device__ __forceinline__ void ld_pkt_if(uint32_t on, uint4& v, const char* p) {
    asm volatile("{.reg .pred q; .reg .b128 r; .reg .b64 lo, hi; setp.ne.u32 q, %5, 0; mov.b64 lo, {%0, %1}; mov.b64 hi, {%2, %3};"
                 " mov.b128 r, {lo, hi}; @q ld.relaxed.gpu.global.b128 r, [%4]; mov.b128 {lo, hi}, r;"
                 " mov.b64 {%0, %1}, lo; mov.b64 {%2, %3}, hi;}"
                 : "+r"(v.x), "+r"(v.y), "+r"(v.z), "+r"(v.w) : "l"(p), "r"(on) : "memory");
}
__device__ __forceinline__ uint4 ld_words(const char* p) {
    uint4 v;
    asm volatile("ld.relaxed.gpu.global.v4.u32 {%0, %1, %2, %3}, [%4];"
                 : "=r"(v.x), "=r"(v.y), "=r"(v.z), "=r"(v.w) : "l"(p) : "memory");
    return v;
}
__device__ __forceinline__ void ld_words_if(uint32_t on, uint4& v, const char* p) {
    asm volatile("{.reg .pred q; setp.ne.u32 q, %5, 0; @q ld.relaxed.gpu.global.v4.u32 {%0, %1, %2, %3}, [%4];}"
                 : "+r"(v.x), "+r"(v.y), "+r"(v.z), "+r"(v.w) : "l"(p), "r"(on) : "memory");
}
__device__ __forceinline__ uint32_t ld_word(const char* p) {
    uint32_t v;
    asm volatile("ld.acquire.gpu.global.u32 %0, [%1];" : "=r"(v) : "l"(p) : "memory");
    return v;
}
__device__ __forceinline__ void st_word(char* p, uint32_t v) {
    asm volatile("st.relaxed.gpu.global.u32 [%0], %1;" ::"l"(p), "r"(v) : "memory");
}
__device__ __forceinline__ void st_word2_if(uint32_t on, char* p, uint32_t v) {
    asm volatile("{.reg .pred q; setp.ne.u32 q, %2, 0; @q st.relaxed.gpu.global.u32 [%0], %1;"
                 " @q st.relaxed.gpu.global.u32 [%0+4096], %1;}" ::"l"(p), "r"(v), "r"(on) : "memory");
}
template <int N, int kWord>
__device__ __forceinline__ void poll_begin(uint4 (&v)[N], const char* p, int stride) {
#pragma unroll
    for (int i = 0; i < N; i++) v[i] = kWord == 4 ? ld_words(p + i * stride) : ld_pkt(p + i * stride);
}
template <int N, int kWord>
__device__ __forceinline__ void poll_end(uint4 (&v)[N], const char* p, int stride, uint32_t tag) {
    while (true) {
        uint32_t bad[N], any = 0;
#pragma unroll
        for (int i = 0; i < N; i++) {
            bad[i] = kWord == 0 ? v[i].x ^ tag : kWord == 3 ? v[i].w ^ tag
                   : ((v[i].x ^ tag) | (v[i].y ^ tag)) | ((v[i].z ^ tag) | (v[i].w ^ tag));
            any |= bad[i];
        }
        if (!__any_sync(0xffffffffu, (any & 31u) != 0)) break;
#pragma unroll
        for (int i = 0; i < N; i++) {
            if (kWord == 4) ld_words_if(bad[i] & 31u, v[i], p + i * stride);
            else ld_pkt_if(bad[i] & 31u, v[i], p + i * stride);
        }
    }
}
template <int N, int kWord>
__device__ __forceinline__ void poll(uint4 (&v)[N], const char* p, int stride, uint32_t tag) {
    poll_begin<N, kWord>(v, p, stride);
    poll_end<N, kWord>(v, p, stride, tag);
}
__device__ __forceinline__ void ldsm4(uint32_t* r, uint32_t a) {
    asm volatile("ldmatrix.sync.aligned.m8n8.x4.shared.b16 {%0, %1, %2, %3}, [%4];"
                 : "=r"(r[0]), "=r"(r[1]), "=r"(r[2]), "=r"(r[3]) : "r"(a));
}
__device__ __forceinline__ void ldsm4t(uint32_t* r, uint32_t a) {
    asm volatile("ldmatrix.sync.aligned.m8n8.x4.trans.shared.b16 {%0, %1, %2, %3}, [%4];"
                 : "=r"(r[0]), "=r"(r[1]), "=r"(r[2]), "=r"(r[3]) : "r"(a));
}
__device__ __forceinline__ uint32_t movm(uint32_t a) {
    uint32_t d;
    asm volatile("movmatrix.sync.aligned.m8n8.trans.b16 %0, %1;" : "=r"(d) : "r"(a));
    return d;
}
__device__ __forceinline__ void mma(float* c, uint32_t a0, uint32_t a1, uint32_t a2, uint32_t a3, uint32_t b0, uint32_t b1) {
    asm("mma.sync.aligned.m16n8k16.row.col.f32.bf16.bf16.f32 {%0, %1, %2, %3}, {%4, %5, %6, %7}, {%8, %9}, {%0, %1, %2, %3};"
        : "+f"(c[0]), "+f"(c[1]), "+f"(c[2]), "+f"(c[3])
        : "r"(a0), "r"(a1), "r"(a2), "r"(a3), "r"(b0), "r"(b1));
}
__device__ __forceinline__ void mma(float* c, const uint32_t* a, uint32_t b0, uint32_t b1) {
    mma(c, a[0], a[1], a[2], a[3], b0, b1);
}
__device__ __forceinline__ void mmav(float* c, const uint32_t* a, uint32_t b0, uint32_t b1) {
    asm volatile("mma.sync.aligned.m16n8k16.row.col.f32.bf16.bf16.f32 {%0, %1, %2, %3}, {%4, %5, %6, %7}, {%8, %9}, {%0, %1, %2, %3};"
                 : "+f"(c[0]), "+f"(c[1]), "+f"(c[2]), "+f"(c[3])
                 : "r"(a[0]), "r"(a[1]), "r"(a[2]), "r"(a[3]), "r"(b0), "r"(b1));
}
__device__ __forceinline__ uint32_t pack_bf16(float lo, float hi) {
    uint32_t d;
    asm("cvt.rn.bf16x2.f32 %0, %1, %2;" : "=r"(d) : "f"(hi), "f"(lo));
    return d;
}
__device__ __forceinline__ float bf_lo(uint32_t v) { return __uint_as_float(v << 16); }
__device__ __forceinline__ float bf_hi(uint32_t v) { return __uint_as_float(v & 0xffff0000u); }
__device__ __forceinline__ float ex2(float x) {
    float y;
    asm("ex2.approx.ftz.f32 %0, %1;" : "=f"(y) : "f"(x));
    return y;
}
__device__ __forceinline__ float lg2(float x) {
    float y;
    asm("lg2.approx.ftz.f32 %0, %1;" : "=f"(y) : "f"(x));
    return y;
}
__device__ __forceinline__ float rcp(float x) {
    float y;
    asm("rcp.approx.ftz.f32 %0, %1;" : "=f"(y) : "f"(x));
    return y;
}
__device__ __forceinline__ float rsq(float x) {
    float y;
    asm("rsqrt.approx.ftz.f32 %0, %1;" : "=f"(y) : "f"(x));
    return y;
}
__device__ __forceinline__ void bar_sync(int id) { asm volatile("bar.sync %0, 256;" ::"r"(id) : "memory"); }
__device__ __forceinline__ void bar_arrive(int id) { asm volatile("bar.arrive %0, 256;" ::"r"(id) : "memory"); }
__device__ __forceinline__ float pick4(const float* v, int i) {
    float a = (i & 1) ? v[1] : v[0];
    float b = (i & 1) ? v[3] : v[2];
    return (i & 2) ? b : a;
}

__device__ __forceinline__ void lds4(uint32_t* v, uint32_t addr) {
    asm volatile("ld.shared.v2.u32 {%0, %1}, [%4]; ld.shared.v2.u32 {%2, %3}, [%4+256];"
                 : "=r"(v[0]), "=r"(v[1]), "=r"(v[2]), "=r"(v[3]) : "r"(addr));
}
__device__ __forceinline__ void arrive_if(uint32_t a, uint32_t on) {
    asm volatile("{.reg .pred p; setp.ne.u32 p, %1, 0; @p mbarrier.arrive.shared::cta.b64 _, [%0];}" ::"r"(a), "r"(on) : "memory");
}
__device__ __forceinline__ void st_pkt_if(uint32_t on, char* p, uint32_t a, uint32_t b, uint32_t c, uint32_t d) {
    asm volatile("{.reg .pred p; .reg .b128 r; .reg .b64 lo, hi; setp.ne.u32 p, %5, 0; mov.b64 lo, {%1, %2}; mov.b64 hi, {%3, %4};"
                 " mov.b128 r, {lo, hi}; @p st.relaxed.gpu.global.b128 [%0], r;}"
                 ::"l"(p), "r"(a), "r"(b), "r"(c), "r"(d), "r"(on) : "memory");
}
__device__ __forceinline__ void load_wq(uint32_t (&wf)[32], uint32_t wa) {
#pragma unroll
    for (int i = 0; i < 4; i++) {
        ldsm4t(&wf[i * 8], wa + i * 1024);
        ldsm4t(&wf[i * 8 + 4], (wa ^ 32) + i * 1024);
    }
}

__host__ __device__ constexpr int tile_buffer(int i) {
    return i < 8 ? SM_K + i * kTile : (i - 8 < kX + 4 ? SM_V + (i - 8) * kTile : SM_K + (i - 8) * kTile);
}
__host__ __device__ constexpr int free_bar(int i) {
    return i < kX ? BAR_EMPTY + i * 8
         : i < kX + 4 ? BAR_EMPTYR + (1 + i - kX) * 8
         : i < 8 ? BAR_EMPTY + (8 + i) * 8
         : i < 8 + kX ? BAR_EMPTY + i * 8
         : i < 8 + kX + kEarly ? BAR_EMPTYR
         : i < 12 + kX ? BAR_EMPTYR + 5 * 8 : BAR_EMPTY + (i - 8) * 8;
}
__host__ __device__ constexpr bool free_prev(int i) { return i < 8 + kX; }
__host__ __device__ constexpr bool can_park(int i) { return (PARKMASK >> i) & 1; }

__host__ __device__ constexpr int early_tile(int i) { return kX + i; }
__host__ __device__ constexpr int late_tile(int i) { return i < kX ? i : 4 + i; }

__device__ __forceinline__ void scores_dual(uint32_t (&bank)[64], const char* qa, float (&s)[2][4], bool mineF, uint32_t empty0,
                                            uint32_t empty1, uint32_t ka, uint32_t kb, int lane) {
    uint32_t qf[16];
#pragma unroll
    for (int i = 0; i < 4; i++) {
        const uint4 u = *reinterpret_cast<const uint4*>(qa + i * 512);
        qf[4 * i] = u.x; qf[4 * i + 1] = u.y; qf[4 * i + 2] = u.z; qf[4 * i + 3] = u.w;
    }
    float b[2][4];
#pragma unroll
    for (int e = 0; e < 4; e++) s[0][e] = s[1][e] = b[0][e] = b[1][e] = 0.f;
#pragma unroll
    for (int j = 0; j < 8; j++) {
        mmav((j & 1) ? b[1] : s[0], &bank[j * 4], qf[2 * j], qf[2 * j + 1]);
        ldsm4(&bank[j * 4], (ka ^ ((j & 3) << 5)) + (j >> 2) * 1024);
    }
    arrive_if(empty0, lane == 0);
#pragma unroll
    for (int j = 0; j < 8; j++) {
        mmav(s[1], &bank[32 + j * 4], qf[2 * j], qf[2 * j + 1]);
        ldsm4(&bank[32 + j * 4], (ka ^ ((j & 3) << 5)) + (j >> 2) * 1024 + kb);
        mmav(b[0], &bank[j * 4], qf[2 * j], qf[2 * j + 1]);
    }
    arrive_if(empty1, lane == 0);
#pragma unroll
    for (int e = 0; e < 4; e++) {
        s[0][e] = mineF ? b[0][e] : s[0][e] + b[1][e];
        b[0][e] = b[1][e] = 0.f;
    }
#pragma unroll
    for (int j = 0; j < 8; j++) mma(b[j & 1], &bank[32 + j * 4], qf[2 * j], qf[2 * j + 1]);
#pragma unroll
    for (int e = 0; e < 4; e++) s[1][e] = mineF ? b[0][e] + b[1][e] : s[1][e];
}

template <bool kRefill>
__device__ __forceinline__ void scores_single(uint32_t (&bank)[64], const char* qa, float (&s)[4], bool low, uint32_t ra) {
    uint32_t qf[8];
#pragma unroll
    for (int i = 0; i < 2; i++) {
        const uint4 u = *reinterpret_cast<const uint4*>(qa + i * 512);
        qf[4 * i] = u.x; qf[4 * i + 1] = u.y; qf[4 * i + 2] = u.z; qf[4 * i + 3] = u.w;
    }
    float a[2][2][4];
#pragma unroll
    for (int e = 0; e < 4; e++) a[0][0][e] = a[0][1][e] = a[1][0][e] = a[1][1][e] = 0.f;
#pragma unroll
    for (int j = 0; j < 4; j++) {
#pragma unroll
        for (int u = 0; u < 4; u++) mma(a[u >> 1][u & 1], &bank[u * 16 + j * 4], qf[2 * j], qf[2 * j + 1]);
        if (kRefill && j < 2) {
            ldsm4t(&bank[j * 4], ra + j * 4096);
            ldsm4t(&bank[16 + j * 4], ra + (4 + j) * 4096);
        }
    }
#pragma unroll
    for (int e = 0; e < 4; e++)
        s[e] = (low ? a[0][0][e] : a[1][1][e]) + __shfl_xor_sync(0xffffffffu, low ? a[1][0][e] : a[0][1][e], 2);
}

__device__ __forceinline__ float sum8(const float* p, int stride) {
    float v[8];
#pragma unroll
    for (int i = 0; i < 8; i++) v[i] = p[i * stride];
    return ((v[0] + v[1]) + (v[2] + v[3])) + ((v[4] + v[5]) + (v[6] + v[7]));
}

__device__ __forceinline__ int order_key(int b) { return b ^ ((b >> 31) & 0x7fffffff); }
__device__ __forceinline__ uint32_t keep(uint32_t v) { return __shfl_sync(0xffffffffu, v, threadIdx.x & 31); }
__device__ __forceinline__ uint32_t tagged_bf16(float v, uint32_t tag) { return pack_bf16(0.f, v) | tag; }
__device__ __forceinline__ uint32_t high_halves(uint32_t a, uint32_t b) { return __byte_perm(a, b, 0x7632); }

__device__ __forceinline__ void cta_max(float& m0, float& m1, uint32_t base, uint32_t col, int lane) {
    float mk = fmaxf((lane & 4) ? m1 : m0, __shfl_xor_sync(0xffffffffu, (lane & 4) ? m0 : m1, 4));
    if (NSH >= 2) mk = fmaxf(mk, __shfl_xor_sync(0xffffffffu, mk, 8));
    if (NSH >= 3) mk = fmaxf(mk, __shfl_xor_sync(0xffffffffu, mk, 16));
    const uint32_t spare = lane & (NSH == 3 ? 24 : NSH == 2 ? 8 : 0);
    asm volatile("red.shared.max.s32 [%0], %1;"
                 ::"r"(base + (spare ? lane * 4 : col + (lane & 4))), "r"(order_key(__float_as_int(mk))) : "memory");
    bar_sync(1);
    int k0, k1;
    asm volatile("ld.shared.v2.u32 {%0, %1}, [%2];" : "=r"(k0), "=r"(k1) : "r"(base + col) : "memory");
    m0 = __int_as_float(order_key(k0));
    m1 = __int_as_float(order_key(k1));
}

__device__ __forceinline__ void consumer(const Params& pr, char* sm, const uint32_t sb) {
    const int w = __shfl_sync(0xffffffffu, threadIdx.x >> 5, 0);
    const int lane = keep(threadIdx.x & 31), tid = w * 32 + lane;
    const int g = lane >> 2, t = lane & 3, mi = lane >> 3, r = lane & 7;
    const int cta = blockIdx.x, h = cta >> 4, c = cta & 15;
    const bool owner = (c & 3) == 0;
    char* const box = reinterpret_cast<char*>((reinterpret_cast<uintptr_t>(g_scratch) + 65535) & ~(uintptr_t)65535);
    const uint32_t myBox = (cta >> 2) * 65536 + (cta & 3) * 16384;
    const uint32_t myGrp = kBoxBytes + h * 16384;

    volatile uint32_t* found = reinterpret_cast<volatile uint32_t*>(sm + SM_PR + 16);
    if (tid < 2) found[tid] = 0;
    asm volatile("bar.sync 7, 256;" ::: "memory");
    if (owner && w >= 6)
        reinterpret_cast<uint32_t*>(sm + SM_X0)[tid - 192] =
            __ldg(reinterpret_cast<const uint32_t*>(pr.x0 + ((tid - 192) >> 3) * 512 + (cta >> 2) * 16) + r);
    if (w == 5 && lane < 8) reinterpret_cast<int*>(sm + SM_M)[lane] = INT_MIN;
    if (w < 4 && lane == 0) {
        char* pa = box + ((w < 2) ? myBox : myGrp) + (w & 1) * 4096 + c * 256;
        st_pkt(pa, 0, 0, 0, 0);
        st_pkt(pa + 16, 0, 0, 0, 0);
        uint32_t best = 0xffffffffu;
#pragma unroll 1
        for (int i = 0; i < NPROBE && !found[w >> 1]; i++) {
            uint32_t t1, old;
            const uint32_t t0 = clock32();
            asm volatile("atom.relaxed.gpu.global.exch.b32 %0, [%1], %2;" : "=r"(old) : "l"(pa), "r"(i << 16) : "memory");
            asm volatile("{.reg .pred p; setp.eq.u32 p, %1, -1; @p exit; mov.u32 %0, %%clock;}" : "=r"(t1) : "r"(old) : "memory");
            best = min(best, t1 - t0);
            if (best < NEARCLK) found[w >> 1] = 1;
        }
        reinterpret_cast<uint32_t*>(sm + SM_PR)[w] = best;
    }
    asm volatile("bar.sync 4, 384;" ::: "memory");
    uint32_t side, gside;
    {
        const uint4 v = *reinterpret_cast<const uint4*>(sm + SM_PR);
        side = v.y < v.x;
        gside = v.w < v.z;
    }
    if (w == 0) { GT(13); }

    const int xcol = 2 * (g & 3) + (t & 1) + 8 * (t >> 1);
    float x = 0.f;
    if (owner) {
        if (lane < 16) x = __uint_as_float(uint32_t(reinterpret_cast<const uint16_t*>(sm + SM_X0)[xcol]) << 16);
        st_word2_if(1, box + (kBoxBytes + w * 16384 + 8192 + (cta >> 2) * 128 + lane * 4), tagged_bf16(x, 1));
    }

    uint32_t bankA[64], bankB[64], res[kRes * 16];
#pragma unroll
    for (int i = 0; i < 64; i++) bankA[i] = bankB[i] = 0;
    const uint32_t woOff = ((mi >> 1) * 8 + r) * kWoPitch + (64 * w + (mi & 1) * 8) * 2;
#pragma unroll 1
    for (int u = 0; u < 4; u++) mbar_wait(sb + BAR_FULLW + u * 8, 0);
#pragma unroll
    for (int u = 0; u < kRes; u++)
#pragma unroll
        for (int i = 0; i < 4; i++) ldsm4t(&res[u * 16 + i * 4], sb + SM_R + woOff + u * 16 * kWoPitch + i * 32);

    const int ch = 2 * w + (mi & 1);
    const uint32_t voff = keep((mi >> 1) * 2048 + (ch >> 3) * 1024 + r * 128 + (((ch & 7) ^ r) << 4));
    const int tile0 = early_tile(w >> 1), tile1 = late_tile(w >> 1);
    const uint32_t ka = keep(sb + SM_K + tile0 * kTile + (w & 1) * 4096 + (mi & 1) * 2048 + r * 128 + (((mi >> 1) ^ r) << 4));
    const uint32_t kb = (tile1 - tile0) * kTile;
    const uint32_t qpw = keep((w * 64 + (t & 1) * 48 + (g >> 1) * 4 + (g & 1) + (t & 2)) * 4);
    const uint32_t qdst = keep(((tid >> 4) & 3) * 512 + (((mi & 1) * 4 + (tid >> 6)) * 4 + t) * 16 + (g & 1) * 8);
    const uint32_t wqa = sb + SM_WQ + (64 * w + (mi >> 1) * 8 + r) * 64 + (((mi & 1) ^ (r >> 1)) << 4);
    float* const qp = reinterpret_cast<float*>(sm + SM_QP);

    uint32_t wf[32];
#pragma unroll 1
    for (int u = 4; u < 16; u++) mbar_wait(sb + BAR_FULLW + u * 8, 0);
    if (w == 0) { GT(10); }
#pragma unroll 1
    for (int T = 1; T >= 0; T--) {
        load_wq(wf, wqa + T * 32768);
        float a0[4] = {0.f, 0.f, 0.f, 0.f}, a1[4] = {0.f, 0.f, 0.f, 0.f};
#pragma unroll
        for (int i = 0; i < 4; i++) {
            mma(a0, &wf[i * 8], kOnes, kOnes);
            mma(a1, &wf[i * 8 + 4], kOnes, kOnes);
        }
        *reinterpret_cast<float*>(sm + SM_QP + qpw) = pick4(a0, t);
        *reinterpret_cast<float*>(sm + SM_QP + (qpw ^ 64)) = pick4(a1, t);
        bar_sync(1);
        if (w == 0) reinterpret_cast<float*>(sm + SM_CS + T * 128)[lane] = sum8(qp + lane, 64) * (1.f / 512.f);
        bar_sync(1);
    }

    if (w == 0) { GT(11); }
    uint32_t ve[kEarly * 8];
#pragma unroll
    for (int i = 0; i < kEarly * 8; i++) ve[i] = 0;
    arrive_if(sb + BAR_EMPTYR, lane == 0);
    uint32_t e1Send = 0, e2Send = 0, tSend = 0;
#pragma unroll 1
    for (int p = 0; p < kPhases; p++) {
        const int T = p & 1;
        const uint32_t tag = p + 1;
        const bool actF = p < 16, actS = p >= 2;
        const int slotF = (p >> 1) & 1;

        {
            TL(0);
            const float cs0 = *reinterpret_cast<const float*>(sm + SM_CS + T * 128 + (qpw & 63));
            const float cs1 = *reinterpret_cast<const float*>(sm + SM_CS + T * 128 + 64 + (qpw & 63));
            const char* xp = box + (myGrp + 8192 + (1 - gside) * 4096 + w * 512 + r * 16);
            wait_until(tSend, owner ? DLY3O : DLY3);
            uint4 xv[4];
            poll<4, 4>(xv, xp, 128, tag);
            TL(1);
            float a[2][2][4], st[2][4];
#pragma unroll
            for (int u = 0; u < 2; u++)
#pragma unroll
                for (int e = 0; e < 4; e++) a[u][0][e] = a[u][1][e] = st[u][e] = 0.f;
#pragma unroll
            for (int i = 0; i < 4; i++) {
                const uint32_t b0 = high_halves(xv[i].x, xv[i].y), b1 = high_halves(xv[i].z, xv[i].w);
                mma(st[i & 1], b0, kOnes, b1, kOnes, b0, b1);
                mma(a[i & 1][0], &wf[i * 8], b0, b1);
                mma(a[i & 1][1], &wf[i * 8 + 4], b0, b1);
            }
            const float sx0 = st[0][2] + st[1][2], sx1 = st[0][3] + st[1][3];
            const float sx = (t & 1) ? sx1 : sx0;
            *reinterpret_cast<float*>(sm + SM_QP + qpw) = fmaf(-sx, cs0, pick4(a[0][0], t)) + pick4(a[1][0], t);
            *reinterpret_cast<float*>(sm + SM_QP + (qpw ^ 64)) = fmaf(-sx, cs1, pick4(a[0][1], t)) + pick4(a[1][1], t);
            if (w < 4) {
                char* dst = box + (myGrp + (w >> 1) * 4096 + c * 256 + (w & 1) * 128 + lane * 4);
                const float* qa = qp + ((w & 1) * 32 + (lane ^ ((w & 1) * 16)));
                bar_sync(2);
                st_word(dst, tagged_bf16(sum8(qa, 64), tag));
            } else {
                bar_arrive(2);
            }
            if ((lane & 27) == 0)
                *reinterpret_cast<float2*>(sm + SM_ST + lane * 16 + w * 8) =
                    make_float2((g & 1) ? sx1 : sx0, (g & 1) ? st[0][1] + st[1][1] : st[0][0] + st[1][0]);
            bar_sync(1);
            if (tid == 0) reinterpret_cast<volatile uint32_t*>(sm + SM_T2)[T] = clock32();
            TL(2);
        }

        {
            uint32_t vf[32];
            const uint32_t ra = sb + SM_RB + voff;
            if (actS) mbar_wait(sb + BAR_FULLR + 5 * 8, T);
#pragma unroll
            for (int i = 0; i < kEarly * 8; i++) vf[i] = ve[i];
#pragma unroll
            for (int i = 2 * kEarly; i < 8; i++) ldsm4t(&vf[i * 4], sb + SM_R + voff + i * 4096);
            arrive_if(sb + BAR_EMPTYR + 5 * 8, lane == 0);
            if (p == 0) {
                const int dst = h * 16 + (tid >> 4);
                uint32_t s1, s2;
                do {
                    s1 = ld_word(box + (kSideTable + dst * 32));
                    s2 = ld_word(box + (kSideTable + (4 * w + t) * 128));
                } while (__any_sync(0xffffffffu, !(s1 & s2 & 1)));
                e1Send = (dst >> 2) * 65536 + (dst & 3) * 16384 + (s1 & 4096) + c * 256 + (t >> 1) * 128 + ((g & 3) * 2 + (t & 1)) * 16;
                e2Send = (4 * w + t) * 65536 + (cta >> 5) * 16384 + 3 * 4096 - (s2 & 4096) + (cta & 31) * 128 + g * 16;
            }
            mbar_wait(sb + (actF ? BAR_FULL + w * 8 : BAR_FULLR + 8 + (w & 3) * 8), T);

            const char* qsrc = box + (myGrp + gside * 4096 + tid * 16);
            uint4 v[1];
            poll_begin<1, 4>(v, qsrc, 0);
            if (w == 7) {
                float2 u = *reinterpret_cast<const float2*>(sm + SM_ST + (lane & 15) * 8);
#pragma unroll
                for (int d = 1; d < 8; d <<= 1) {
                    u.x += __shfl_xor_sync(0xffffffffu, u.x, d);
                    u.y += __shfl_xor_sync(0xffffffffu, u.y, d);
                }
                const float mean = u.x * (1.f / 512.f);
                const float var = fmaxf(fmaf(-mean, mean, u.y * (1.f / 512.f)), 0.f);
                if ((lane & 23) == 0) reinterpret_cast<float*>(sm + SM_SC)[mi] = rsq(var + 1e-5f) * kScale;
            }
            if (p == kPhases - 1) {
                mbar_wait(sb + BAR_FULLR + 8, T);
                mbar_wait(sb + BAR_FULLR + 24, T);
#pragma unroll
                for (int j = 0; j < 2; j++) {
                    ldsm4t(&bankA[j * 4], ra + j * 4096);
                    ldsm4t(&bankA[16 + j * 4], ra + (4 + j) * 4096);
                }
            }
            poll_end<1, 4>(v, qsrc, 0, tag);
            *reinterpret_cast<uint2*>(sm + SM_Q + qdst) = make_uint2(high_halves(v[0].x, v[0].y), high_halves(v[0].z, v[0].w));
            bar_sync(1);
            TL(3);
            const bool mineF = (t >> 1) == slotF;
            const uint32_t sendE1 = mineF ? actF : actS;
            const uint32_t pa = sb + SM_P + lane * 8;
            float o[4], m0, m1, r0, r1;
            uint32_t e0, e1;
            auto finishL = [&](float l0, float l1) {
                r0 = rcp(l0);
                r1 = rcp(l1);
                e0 = __float_as_uint(m0 + lg2(l0));
                e1 = (__float_as_uint(m1 + lg2(l1)) & ~31u) | tag;
            };
            if (actF) {
                const float sc = reinterpret_cast<const float*>(sm + SM_SC)[t >> 1];
                float s[2][4];
                const char* qa = sm + SM_Q + lane * 16;
                if (T) scores_dual(bankB, qa, s, mineF, sb + BAR_EMPTY + tile0 * 8, sb + BAR_EMPTY + tile1 * 8, ka, kb, lane);
                else scores_dual(bankA, qa, s, mineF, sb + BAR_EMPTY + tile0 * 8, sb + BAR_EMPTY + tile1 * 8, ka, kb, lane);
                TL(4);
                m0 = fmaxf(fmaxf(s[0][0], s[0][2]), fmaxf(s[1][0], s[1][2]));
                m1 = fmaxf(fmaxf(s[0][1], s[0][3]), fmaxf(s[1][1], s[1][3]));
                cta_max(m0, m1, sb + SM_M, t * 8, lane);
                m0 *= sc;
                m1 *= sc;
                {
                    uint32_t pk[4];
#pragma unroll
                    for (int u = 0; u < 2; u++) {
                        pk[2 * u] = movm(pack_bf16(ex2(fmaf(s[u][0], sc, -m0)), ex2(fmaf(s[u][1], sc, -m1))));
                        pk[2 * u + 1] = movm(pack_bf16(ex2(fmaf(s[u][2], sc, -m0)), ex2(fmaf(s[u][3], sc, -m1))));
                    }
                    char* pw = sm + SM_P + (w & 1) * 256 + lane * 8;
                    *reinterpret_cast<uint2*>(pw + tile0 * 512) = make_uint2(pk[0], pk[1]);
                    *reinterpret_cast<uint2*>(pw + tile1 * 512) = make_uint2(pk[2], pk[3]);
                }
                bar_sync(1);
                TL(5);

                float la[4] = {0.f, 0.f, 0.f, 0.f}, lb[4] = {0.f, 0.f, 0.f, 0.f};
                float sa[4] = {0.f, 0.f, 0.f, 0.f}, fa[4] = {0.f, 0.f, 0.f, 0.f}, fb[4] = {0.f, 0.f, 0.f, 0.f};
                uint32_t pk[2][4], va[2][8];
                const uint32_t vbase = sb + voff;
                lds4(pk[0], pa);
#pragma unroll
                for (int i = 0; i <= 8; i++) {
                    if (i < 8) {
                        mma(sa, &vf[(i & 3) * 8], pk[i & 1][0], pk[i & 1][1]);
                        mma(la, kOnes, kOnes, kOnes, kOnes, pk[i & 1][0], pk[i & 1][1]);
                        mma(sa, &vf[(i & 3) * 8 + 4], pk[i & 1][2], pk[i & 1][3]);
                        mma(lb, kOnes, kOnes, kOnes, kOnes, pk[i & 1][2], pk[i & 1][3]);
                        if (i == 7) finishL(la[0] + lb[0], la[1] + lb[1]);
                        mbar_wait(sb + BAR_FULL + (8 + i) * 8, T);
                        ldsm4t(va[i & 1], vbase + tile_buffer(8 + i));
                        ldsm4t(va[i & 1] + 4, vbase + tile_buffer(8 + i) + 4096);
                        arrive_if(sb + BAR_EMPTY + (8 + i) * 8, lane == 0);
                        if (i >= 3 && i < 7) {
                            if (actS) mbar_wait(sb + BAR_FULLR + (i - 2) * 8, T);
                            ldsm4t(&vf[(i - 3) * 8], ra + (i - 3) * kTile);
                            ldsm4t(&vf[(i - 3) * 8 + 4], ra + (i - 3) * kTile + 4096);
                            arrive_if(sb + BAR_EMPTYR + (i - 2) * 8, lane == 0);
                        }
                    }
                    if (i > 0) {
                        mma(fa, va[(i - 1) & 1], pk[(i - 1) & 1][0], pk[(i - 1) & 1][1]);
                        mma(fb, va[(i - 1) & 1] + 4, pk[(i - 1) & 1][2], pk[(i - 1) & 1][3]);
                    }
                    if (i < 7) lds4(pk[(i + 1) & 1], pa + (i + 1) * 512);
                }
#pragma unroll
                for (int e = 0; e < 4; e++) o[e] = mineF ? fa[e] + fb[e] : sa[e];
            } else {
                const float sc = reinterpret_cast<const float*>(sm + SM_SC)[1];
                const bool low = t < 2;
                float s[4];
                const char* qa = sm + SM_Q + (lane >> 4) * 1024 + 256 + (lane & 15) * 16;
                if (T) scores_single<false>(bankB, qa, s, low, ra);
                else scores_single<true>(bankA, qa, s, low, ra);
                TL(4);
                m0 = fmaxf(s[0], s[2]);
                m1 = fmaxf(s[1], s[3]);
                cta_max(m0, m1, sb + SM_M, (t & 1) * 8, lane);
                m0 *= sc;
                m1 *= sc;
                *reinterpret_cast<uint2*>(sm + SM_P + tid * 8) =
                    make_uint2(movm(pack_bf16(ex2(fmaf(s[0], sc, -m0)), ex2(fmaf(s[1], sc, -m1)))),
                               movm(pack_bf16(ex2(fmaf(s[2], sc, -m0)), ex2(fmaf(s[3], sc, -m1)))));
                bar_sync(1);
                TL(5);
                uint32_t pk[4][4];
                float acc[4][4], la[2][4];
#pragma unroll
                for (int i = 0; i < 4; i++) {
                    lds4(pk[i], pa + i * 512);
#pragma unroll
                    for (int e = 0; e < 4; e++) acc[i][e] = la[i & 1][e] = 0.f;
                }
#pragma unroll
                for (int j = 2; j < 4; j++) {
                    ldsm4t(&bankA[j * 4], ra + j * 4096);
                    ldsm4t(&bankA[16 + j * 4], ra + (4 + j) * 4096);
                }
                arrive_if(sb + BAR_EMPTYR + 8 + t * 8, lane < 4);
                const uint32_t ones[4] = {kOnes, kOnes, kOnes, kOnes};
#pragma unroll
                for (int i = 0; i < 4; i++)
#pragma unroll
                    for (int u = 0; u < 2; u++) {
                        const int j0 = early_tile(i);
                        mmav(la[u], ones, pk[i][2 * u], pk[i][2 * u + 1]);
                        mmav(acc[u], j0 < 4 ? &vf[j0 * 8 + u * 4] : &bankA[(j0 - 4) * 8 + u * 4], pk[i][2 * u], pk[i][2 * u + 1]);
                    }
#pragma unroll
                for (int k = 0; k < 4; k++)
#pragma unroll
                    for (int u = 0; u < 2; u++) {
                        const int i = (k >> 1) | ((k & 1) << 1), j1 = late_tile(i);
                        mmav(acc[2 + u], j1 < 4 ? &vf[j1 * 8 + u * 4] : &bankA[(j1 - 4) * 8 + u * 4], pk[i][2 * u], pk[i][2 * u + 1]);
                    }
                float l0 = la[0][0] + la[1][0], l1 = la[0][1] + la[1][1];
                l0 += __shfl_xor_sync(0xffffffffu, l0, 2);
                l1 += __shfl_xor_sync(0xffffffffu, l1, 2);
                finishL(l0, l1);
#pragma unroll
                for (int e = 0; e < 4; e++)
                    o[e] = (acc[2][e] + acc[3][e]) + __shfl_xor_sync(0xffffffffu, acc[0][e] + acc[1][e], 2);
            }
            TL(8);
            if (w == 0 && (p == 0 || p == 15)) { GT(p ? 15 : 9); }
            st_pkt_if(sendE1, box + e1Send, pack_bf16(o[0] * r0, o[1] * r1), pack_bf16(o[2] * r0, o[3] * r1), e0, e1);
            tSend = clock32();
            if (lane < 8) reinterpret_cast<int*>(sm + SM_M)[lane] = INT_MIN;
            bar_sync(1);
        }

        {
            if (T) {
#pragma unroll
                for (int i = 0; i < 8; i++) ldsm4t(&wf[i * 4], sb + SM_WOB + woOff + (i >> 2) * 16 * kWoPitch + (i & 3) * 32);
            } else {
#pragma unroll
                for (int i = 0; i < 4 * (2 - kRes); i++) ldsm4t(&wf[i * 4], sb + SM_WOA + woOff + i * 32);
#pragma unroll
                for (int i = 0; i < 16 * kRes; i++) wf[16 * (2 - kRes) + i] = res[i];
            }
            if (w < 2) {
                uint2 o2 = make_uint2(0, 0);
                if (w == slotF ? actF : actS) {
                    const char* src = box + (myBox + side * 4096 + mi * 256 + w * 128 + r * 16);
                    uint4 v[4];
                    poll<4, 3>(v, src, 1024, tag);
                    TLW(9);
                    float e0[4], e1[4];
#pragma unroll
                    for (int i = 0; i < 4; i++) {
                        e0[i] = __uint_as_float(v[i].z);
                        e1[i] = __uint_as_float(v[i].w);
                    }
                    float m0 = fmaxf(fmaxf(e0[0], e0[1]), fmaxf(e0[2], e0[3]));
                    float m1 = fmaxf(fmaxf(e1[0], e1[1]), fmaxf(e1[2], e1[3]));
#pragma unroll
                    for (int d = 8; d < 32; d <<= 1) {
                        m0 = fmaxf(m0, __shfl_xor_sync(0xffffffffu, m0, d));
                        m1 = fmaxf(m1, __shfl_xor_sync(0xffffffffu, m1, d));
                    }
                    float w0 = ex2(e0[0] - m0), w1 = ex2(e1[0] - m1);
                    float o[4] = {w0 * bf_lo(v[0].x), w1 * bf_hi(v[0].x), w0 * bf_lo(v[0].y), w1 * bf_hi(v[0].y)};
#pragma unroll
                    for (int i = 1; i < 4; i++) {
                        const float a = ex2(e0[i] - m0), b = ex2(e1[i] - m1);
                        w0 += a;
                        w1 += b;
                        o[0] = fmaf(a, bf_lo(v[i].x), o[0]);
                        o[1] = fmaf(b, bf_hi(v[i].x), o[1]);
                        o[2] = fmaf(a, bf_lo(v[i].y), o[2]);
                        o[3] = fmaf(b, bf_hi(v[i].y), o[3]);
                    }
#pragma unroll
                    for (int d = 8; d < 32; d <<= 1) {
                        w0 += __shfl_xor_sync(0xffffffffu, w0, d);
                        w1 += __shfl_xor_sync(0xffffffffu, w1, d);
#pragma unroll
                        for (int e = 0; e < 4; e++) o[e] += __shfl_xor_sync(0xffffffffu, o[e], d);
                    }
                    const float r0 = rcp(w0), r1 = rcp(w1);
                    o2 = make_uint2(pack_bf16(o[0] * r0, o[1] * r1), pack_bf16(o[2] * r0, o[3] * r1));
                }
                if (lane < 8) *reinterpret_cast<uint2*>(sm + SM_O + w * 64 + lane * 8) = o2;
            }
            bar_sync(1);
            TL(10);
            const uint4 ob = *reinterpret_cast<const uint4*>(sm + SM_O + r * 16);
            float y[4][4];
#pragma unroll
            for (int i = 0; i < 4; i++) {
#pragma unroll
                for (int e = 0; e < 4; e++) y[i][e] = 0.f;
                mma(y[i], &wf[i * 4], ob.x, ob.y);
            }
#pragma unroll
            for (int i = 0; i < 4; i++) mma(y[i], &wf[16 + i * 4], ob.z, ob.w);
            float z[4];
#pragma unroll
            for (int e = 0; e < 4; e++) {
                const float a = (t & 1) ? y[1][e] : y[0][e];
                const float b = (t & 1) ? y[3][e] : y[2][e];
                z[e] = (t & 2) ? b : a;
            }
            st_pkt(box + e2Send, (__float_as_uint(z[0]) & ~31u) | tag, __float_as_uint(z[1]), __float_as_uint(z[2]),
                   __float_as_uint(z[3]));
            tSend = clock32();
            TL(11);
        }

        const bool last = p + 1 == kPhases;
        if (last && !owner) break;
        if (!last) {
            bar_sync(1);
            if (p >= 1) mbar_wait(sb + BAR_FULLR, T ^ 1);
        }
#pragma unroll
        for (int i = 0; i < 2 * kEarly; i++) ldsm4t(&ve[i * 4], sb + SM_R + voff + i * 4096);
        arrive_if(sb + BAR_EMPTYR, lane == 0);
        if (!owner) {
            load_wq(wf, wqa + (T ^ 1) * 32768);
        } else {
            const char* src = box + (myBox + (3 - side) * 4096 + tid * 16);
            uint4 v[4];
            wait_until(tSend, DLY2);
            poll_begin<4, 0>(v, src, 16384);
            load_wq(wf, wqa + (T ^ 1) * 32768);
            poll_end<4, 0>(v, src, 16384, tag);
            TL(12);
            float z[4];
            z[0] = (__uint_as_float(v[0].x ^ tag) + __uint_as_float(v[1].x ^ tag)) +
                   (__uint_as_float(v[2].x ^ tag) + __uint_as_float(v[3].x ^ tag));
            z[1] = (__uint_as_float(v[0].y) + __uint_as_float(v[1].y)) + (__uint_as_float(v[2].y) + __uint_as_float(v[3].y));
            z[2] = (__uint_as_float(v[0].z) + __uint_as_float(v[1].z)) + (__uint_as_float(v[2].z) + __uint_as_float(v[3].z));
            z[3] = (__uint_as_float(v[0].w) + __uint_as_float(v[1].w)) + (__uint_as_float(v[2].w) + __uint_as_float(v[3].w));
            const float k0 = (mi & 1) ? z[1] : z[0], k1 = (mi & 1) ? z[3] : z[2];
            const float g0 = (mi & 1) ? z[0] : z[1], g1 = (mi & 1) ? z[2] : z[3];
            const float u0 = k0 + __shfl_xor_sync(0xffffffffu, g0, 8), u1 = k1 + __shfl_xor_sync(0xffffffffu, g1, 8);
            const float zz = ((mi & 2) ? u1 : u0) + __shfl_xor_sync(0xffffffffu, (mi & 2) ? u0 : u1, 16);
            float* red = reinterpret_cast<float*>(sm + SM_RED);
            red[w * 32 + (mi & 1) * 16 + (r >> 1) * 4 + (mi & 2) + (r & 1)] = zz;
            char* dst3 = box + (kBoxBytes + w * 16384 + 8192 + (cta >> 2) * 128 + lane * 4);
            const bool retire = T && (lane >> 4) != slotF;
            const uint32_t nx = uint32_t(reinterpret_cast<const uint16_t*>(sm + SM_X0)[(((p + 1) >> 1) & 7) * 16 + xcol]) << 16;
            __nv_bfloat16* dst = pr.out + (((p >> 1) - 1) * 512 + (cta >> 2) * 16 + xcol);
            const uint32_t emit = retire && actS && w == 0;
            bar_sync(1);
            x += sum8(red + lane, 32);
            const uint32_t xb = pack_bf16(0.f, x);
            st_word2_if(!last, dst3, (retire ? nx : xb) | (tag + 1));
            asm volatile("{.reg .pred p; setp.ne.u32 p, %2, 0; @p st.global.u16 [%0], %1;}"
                         ::"l"(dst), "h"((unsigned short)(xb >> 16)), "r"(emit) : "memory");
            if (retire) x = __uint_as_float(nx);
            tSend = clock32();
            TL(13);
        }
    }
    if (lane == 0) mbar_arrive(sb + BAR_DONE);
}

__device__ __forceinline__ bool handshake(uint32_t addr) {
    uint32_t old;
    asm volatile("atom.shared.add.u32 %0, [%1], 1;" : "=r"(old) : "r"(addr) : "memory");
    return old & 1;
}

template <int I>
__device__ __forceinline__ void load_tile(const Params& pr, uint32_t sb, int p, int grp, uint64_t polF, uint64_t polN) {
    mbar_expect(sb + BAR_FULL + I * 8, kTile);
    tma_kv(sb + tile_buffer(I), &pr.kv[(p & 1) * 2 + (I >> 3)], grp + (I & 7) * 4,
           sb + BAR_FULL + I * 8, I < 8 ? polF : polN);
}

__host__ __device__ constexpr bool unit_is_wq(int u) { return WORDER == 0 ? u >= 8 : (WORDER == 1 ? ((u >> 2) & 1) : (u >= 4 && u < 12)); }
__host__ __device__ constexpr int unit_layer(int u) { return WORDER == 0 ? (u >> 2) & 1 : u >> 3; }
template <int U>
__device__ __forceinline__ void load_weight_unit(const Params& pr, const uint32_t sb, uint64_t polF) {
    constexpr int T = unit_layer(U), q = U & 3, half = q >> 1;
    const int h = blockIdx.x >> 4, c = blockIdx.x & 15;
    const uint32_t bar = sb + BAR_FULLW + U * 8;
    if ((U & 1) == 0) { GT(1 + U / 2); }
    mbar_expect(bar, kTile);
    if constexpr (unit_is_wq(U)) {
        tma_2d(sb + SM_WQ + T * 32768 + q * kTile, &pr.wq[T], h * 512 + c * 32, q * 128, bar, polF);
    } else {
        constexpr int dst = T ? SM_WOB + half * 16 * kWoPitch
                              : (half < 2 - kRes ? SM_WOA : SM_R + (half - (2 - kRes)) * 16 * kWoPitch);
        const __nv_bfloat16* src = pr.wo[T] + (size_t)(h * 512 + q * 128 + 16 * (c >> 1) + 4 * (c & 1)) * 512;
#pragma unroll
        for (int k = 0; k < 8; k++)
            bulk_1d(sb + dst + (2 * k + (q & 1)) * kWoPitch, src + (8 * (k >> 2) + (k & 3)) * 512, 1024, bar, polF);
    }
}

template <int N>
__device__ __forceinline__ void startup_window(uint32_t sb, uint32_t t0) {
    auto landBar = [&](int j) { return sb + (j < 16 ? BAR_FULLW : BAR_FULL) + (j & 15) * 8; };
    constexpr int lo = N - SPAN + 1 < 0 ? 0 : N - SPAN + 1;
    if constexpr (N >= SPAN) mbar_wait(landBar(N - SPAN), 0);
    while (true) {
        uint32_t landed = 0;
#pragma unroll
        for (int j = lo; j < N; j++) landed += mbar_test(landBar(j), 0);
        const bool late = (int)(clock32() - t0) >= SCA0 + SCB0 * N;
        if (N - lo - landed < (late ? WMAX0 : WIN0) - (N < 16 && unit_is_wq(N) ? WQW : 0) + (N >= 16 ? (WMASK >> (N & 15)) & 1 : 0)) break;
    }
}

template <int U>
__device__ __forceinline__ void load_weights(const Params& pr, const uint32_t sb, uint64_t polF, uint32_t t0) {
    startup_window<U>(sb, t0);
    load_weight_unit<U>(pr, sb, polF);
    if constexpr (U < 15) load_weights<U + 1>(pr, sb, polF, t0);
}

template <int I>
__device__ __forceinline__ void wait_free(uint32_t sb, int p) {
    if (!free_prev(I)) mbar_wait(sb + free_bar(I), p & 1);
    else if (p > 0) mbar_wait(sb + free_bar(I), (p - 1) & 1);
}

template <int I, bool kFirst>
__device__ __forceinline__ void request_tiles(const Params& pr, uint32_t sb, int p, int grp, uint64_t polF, uint64_t polN,
                                              uint32_t t0) {
    uint32_t hs = 0;
    if constexpr (kFirst) {
        startup_window<16 + I>(sb, t0);
    } else {
        auto landBar = [&](int j) { return sb + BAR_FULL + (j & 15) * 8; };
        mbar_wait(landBar(I - SPAN), (I - SPAN >= 0 ? p : p - 1) & 1);
        while (true) {
            uint32_t t2, landed = 0;
            const uint32_t now = clock32();
            asm volatile("ld.volatile.shared.u32 %0, [%1];" : "=r"(hs) : "r"(sb + SM_HS + I * 4) : "memory");
            asm volatile("ld.volatile.shared.u32 %0, [%1];" : "=r"(t2) : "r"(sb + SM_T2 + ((p - 1) & 1) * 4) : "memory");
#pragma unroll
            for (int j = I - SPAN + 1; j < I; j++) landed += mbar_test(landBar(j), (j >= 0 ? p : p - 1) & 1);
            if (T20 && p == 1) t2 = t0 + T20;
            const bool late = (hs & 1) && (int)(now - t2) >= SCHA + SCHB * I;
            if (SPAN - 1 - landed < (late ? kWinMax : kWin) + ((WMASK >> I) & 1)) break;
        }
    }
    if ((hs & 1) || handshake(sb + SM_HS + I * 4)) {
        load_tile<I>(pr, sb, p, grp, polF, polN);
        if (hs & 1) asm volatile("red.shared.add.u32 [%0], 1;" ::"r"(sb + SM_HS + I * 4) : "memory");
    } else {
        prefetch_l2(pr.kvp[(p & 1) * 2 + (I >> 3)] + (size_t)(grp + (I & 7) * 4) * 2048, kTile, polN);
    }
    if constexpr (I < 15) request_tiles<I + 1, kFirst>(pr, sb, p, grp, polF, polN, t0);
}

__device__ __forceinline__ void requester(const Params& pr, const uint32_t sb, uint32_t t0) {
    const uint64_t polF = policy_first(), polN = policy_normal();
    const int grp0 = (blockIdx.x >> 4) * 512 + (blockIdx.x & 15) * 32;
    request_tiles<0, true>(pr, sb, 0, grp0, polF, polN, t0);
#pragma unroll 1
    for (int p = 1; p < 16; p++) request_tiles<0, false>(pr, sb, p, (p >> 1) * 4096 + grp0, polF, polN, t0);
}

template <int I>
__device__ __forceinline__ void unpark_tiles(const Params& pr, uint32_t sb, int p, int grp, uint64_t polF, uint64_t polN) {
    if constexpr (can_park(I)) {
        wait_free<I>(sb, p);
        if (handshake(sb + SM_HS + I * 4)) load_tile<I>(pr, sb, p, grp, polF, polN);
    }
    if constexpr (I < 15) unpark_tiles<I + 1>(pr, sb, p, grp, polF, polN);
}

__device__ __forceinline__ void parked_loader(const Params& pr, const uint32_t sb) {
    const uint64_t polF = policy_first(), polN = policy_normal();
    const int grp0 = (blockIdx.x >> 4) * 512 + (blockIdx.x & 15) * 32;
#pragma unroll 1
    for (int p = 0; p < 16; p++) unpark_tiles<0>(pr, sb, p, (p >> 1) * 4096 + grp0, polF, polN);
}

__device__ __forceinline__ void bounded_wait(uint32_t a, uint32_t parity) {
    uint32_t spins = 0;
    while (!mbar_try(a, parity))
        if (++spins > kSpinLimit) fault();
}

__device__ __forceinline__ void reread_producer(const Params& pr, const uint32_t sb) {
    static_assert(RGATE >= kX + 3, "the first half reuses the buffers of V tiles kX..kX+3");
    const uint64_t polF = policy_first();
    const int grp0 = (blockIdx.x >> 4) * 512 + (blockIdx.x & 15) * 32;
    bounded_wait(sb + BAR_EMPTY + (8 + RGATE) * 8, 0);
#pragma unroll 1
    for (int p = 2; p < kPhases; p++) {
        const int T = p & 1;
        const int g0 = ((p >> 1) - 1) * 4096 + grp0;
        bounded_wait(sb + (p <= 16 ? BAR_EMPTY + (8 + RGATE) * 8 : BAR_EMPTYR + 8), T ^ 1);
        mbar_expect(sb + BAR_FULLR, kEarly * kTile);
        mbar_expect(sb + BAR_FULLR + 5 * 8, (4 - kEarly) * kTile);
#pragma unroll 1
        for (int i = 0; i < 4; i++) {
            const uint32_t t0 = clock32();
            tma_kv(sb + SM_R + i * kTile, &pr.kv[2 * T + 1], g0 + i * 4, sb + BAR_FULLR + (i < kEarly ? 0 : 5 * 8), polF);
            wait_until(t0, p < 16 ? (i + 1 < kEarly ? RGAPA : RGAP) : RGAPB);
        }
#pragma unroll
        for (int i = 0; i < 4; i++) {
            const uint32_t t0 = clock32();
            bounded_wait(sb + (p < 16 ? BAR_EMPTY + (kX + i) * 8 : BAR_EMPTYR + (1 + i) * 8), p < 16 ? T : T ^ 1);
            mbar_expect(sb + BAR_FULLR + (1 + i) * 8, kTile);
            tma_kv(sb + SM_RB + i * kTile, &pr.kv[2 * T + 1], g0 + 16 + i * 4, sb + BAR_FULLR + (1 + i) * 8, polF);
            if (p >= 16) wait_until(t0, RGAPB);
        }
    }
    bounded_wait(sb + BAR_DONE, 0);
}

__device__ __forceinline__ void mailbox_setup(const char* sm, const uint32_t sb) {
    const int lane = threadIdx.x & 31, cta = blockIdx.x;
    char* const box = reinterpret_cast<char*>((reinterpret_cast<uintptr_t>(g_scratch) + 65535) & ~(uintptr_t)65535);
    const uint2 v = *reinterpret_cast<const uint2*>(sm + SM_PR);
    const uint32_t side = v.y < v.x;
    char* mine = box + ((cta >> 2) * 65536 + (cta & 3) * 16384 + lane * 16);
#pragma unroll
    for (int i = 0; i < 8; i++) st_pkt(mine + (side * 4096 + i * 512), 0, 0, 0, 0);
    if ((cta & 3) == 0) {
#pragma unroll 1
        for (int q = 0; q < 4; q++)
#pragma unroll
            for (int i = 0; i < 8; i++) st_pkt(mine + (q * 16384 + (3 - side) * 4096 + i * 512), 0, 0, 0, 0);
    }
    __threadfence();
    __syncwarp();
    if (lane < 8) st_word(box + (kSideTable + cta * 32 + lane * 4), 1 | (side << 12));
    GT(14);
    mbar_wait(sb + BAR_EMPTY + 15 * 8, 0);
    mbar_wait(sb + BAR_EMPTY + 15 * 8, 1);
    if (lane < 8) st_word(box + (kSideTable + cta * 32 + lane * 4), 0);
}

__global__ void __launch_bounds__(kThreads, 1) decode_kernel(const __grid_constant__ Params pr) {
    extern __shared__ __align__(1024) char smem[];
    constexpr uint32_t sb = 1024;
    if ((uint32_t)__cvta_generic_to_shared(smem) != sb) fault();
    const int w = __shfl_sync(0xffffffffu, threadIdx.x >> 5, 0), lane = threadIdx.x & 31;
    const uint32_t tStart = clock32();
    if (w == 11 && elect_one()) {
        GT(0);
#pragma unroll
        for (int i = 0; i < 4; i++) mbar_init(sb + BAR_FULLW + i * 8, 1);
        asm volatile("fence.mbarrier_init.release.cluster;" ::: "memory");
        const uint64_t polF = policy_first();
        load_weight_unit<0>(pr, sb, polF);
        load_weight_unit<1>(pr, sb, polF);
        load_weight_unit<2>(pr, sb, polF);
        load_weight_unit<3>(pr, sb, polF);
    }
    if (w >= 8) {
        asm volatile("setmaxnreg.dec.sync.aligned.u32 24;");
        if (w == 11) {
            asm volatile("bar.arrive 4, 384;" ::: "memory");
            asm volatile("bar.sync 6, 64;" ::: "memory");
            if (elect_one()) {
                load_weights<4>(pr, sb, policy_first(), tStart);
                requester(pr, sb, tStart);
            }
        } else {
            if (w == 10) {
                if (lane < 16) reinterpret_cast<uint32_t*>(smem + SM_HS)[lane] = 0;
                if (elect_one()) {
#pragma unroll
                    for (int i = 0; i < 6; i++) asm volatile("prefetch.tensormap [%0];" ::"l"(&pr.kv[0] + (i + 4) % 6) : "memory");
#pragma unroll
                    for (int i = 0; i < 16; i++) {
                        mbar_init(sb + BAR_FULL + i * 8, 1);
                        mbar_init(sb + BAR_EMPTY + i * 8, i < 8 ? 2 : 8);
                        if (i >= 4) mbar_init(sb + BAR_FULLW + i * 8, 1);
                    }
#pragma unroll
                    for (int i = 0; i < 6; i++) {
                        mbar_init(sb + BAR_FULLR + i * 8, 1);
                        mbar_init(sb + BAR_EMPTYR + i * 8, 8);
                    }
                    mbar_init(sb + BAR_DONE, 8);
                    asm volatile("fence.mbarrier_init.release.cluster;" ::: "memory");
                }
                __syncwarp();
                asm volatile("bar.arrive 6, 64;" ::: "memory");
            }
            asm volatile("bar.sync 4, 384;" ::: "memory");
            if (w == 8) {
                mailbox_setup(smem, sb);
            } else if (elect_one()) {
                if (w == 10) parked_loader(pr, sb);
                else reread_producer(pr, sb);
            }
        }
    } else {
        asm volatile("setmaxnreg.inc.sync.aligned.u32 240;");
        consumer(pr, static_cast<char*>(__cvta_shared_to_generic(sb)), sb);
    }
}

typedef CUresult (*EncodeFn)(CUtensorMap*, CUtensorMapDataType, cuuint32_t, void*, const cuuint64_t*, const cuuint64_t*,
                             const cuuint32_t*, const cuuint32_t*, CUtensorMapInterleave, CUtensorMapSwizzle,
                             CUtensorMapL2promotion, CUtensorMapFloatOOBfill);

void encode_kv(EncodeFn fn, CUtensorMap* m, void* base) {
    const cuuint64_t dims[4] = {64, 8, 2, 32768};
    const cuuint64_t strides[3] = {256, 128, 2048};
    const cuuint32_t box[4] = {64, 8, 2, 4};
    const cuuint32_t es[4] = {1, 1, 1, 1};
    fn(m, CU_TENSOR_MAP_DATA_TYPE_BFLOAT16, 4, base, dims, strides, box, es, CU_TENSOR_MAP_INTERLEAVE_NONE,
       CU_TENSOR_MAP_SWIZZLE_128B, CU_TENSOR_MAP_L2_PROMOTION_NONE, CU_TENSOR_MAP_FLOAT_OOB_FILL_NONE);
}

void encode_wq(EncodeFn fn, CUtensorMap* m, void* base) {
    const cuuint64_t dims[2] = {4096, 512};
    const cuuint64_t strides[1] = {8192};
    const cuuint32_t box[2] = {32, 128};
    const cuuint32_t es[2] = {1, 1};
    fn(m, CU_TENSOR_MAP_DATA_TYPE_BFLOAT16, 2, base, dims, strides, box, es, CU_TENSOR_MAP_INTERLEAVE_NONE,
       CU_TENSOR_MAP_SWIZZLE_64B, CU_TENSOR_MAP_L2_PROMOTION_NONE, CU_TENSOR_MAP_FLOAT_OOB_FILL_NONE);
}

}

extern "C" void kernel_launch(void* const* d_in, const int* in_sizes, int n_in, void* d_out, int out_size) {
    static EncodeFn encode = nullptr;
    if (!encode) {
        void* fn = nullptr;
        cudaDriverEntryPointQueryResult st;
        cudaGetDriverEntryPoint("cuTensorMapEncodeTiled", &fn, cudaEnableDefault, &st);
        encode = reinterpret_cast<EncodeFn>(fn);
        cudaFuncSetAttribute(decode_kernel, cudaFuncAttributeMaxDynamicSharedMemorySize, SM_TOTAL);
    }
    Params pr;
    const int kvIdx[4] = {1, 2, 6, 7};
    for (int i = 0; i < 4; i++) {
        encode_kv(encode, &pr.kv[i], d_in[kvIdx[i]]);
        pr.kvp[i] = static_cast<const char*>(d_in[kvIdx[i]]);
    }
    encode_wq(encode, &pr.wq[0], d_in[3]);
    encode_wq(encode, &pr.wq[1], d_in[8]);
    pr.wo[0] = static_cast<const __nv_bfloat16*>(d_in[4]);
    pr.wo[1] = static_cast<const __nv_bfloat16*>(d_in[9]);
    pr.x0 = static_cast<const __nv_bfloat16*>(d_in[0]);
    pr.out = static_cast<__nv_bfloat16*>(d_out);
    decode_kernel<<<kCtas, kThreads, SM_TOTAL>>>(pr);
}
```
